```python
import torch

def _softmax(x, axis=-1):
    return torch.softmax(x, dim=axis)
def _gelu(x):
    return torch.nn.functional.gelu(x, approximate="tanh")
def _silu(x):
    return torch.nn.functional.silu(x)
def _sigmoid(x):
    return torch.sigmoid(x)
def _layernorm(x, axis=-1, eps=1e-5):
    m = x.mean(dim=axis, keepdim=True)
    v = x.var(dim=axis, keepdim=True, unbiased=False)
    return (x - m) / torch.sqrt(v + eps)
def _scatter_add(tgt, idx, src, axis=0):
    return tgt.clone().index_add_(axis, idx, src)
def _segment_sum(src, seg, n):
    out = torch.zeros((n,) + src.shape[1:], dtype=src.dtype)
    return out.index_add_(0, seg, src)
def _pad(x, pw):
    flat = tuple(v for pair in reversed(pw) for v in pair)
    return torch.nn.functional.pad(x, flat)

kernel_name = 'concat_heads__mha_block_cached__mha_block_cached__near_ridge'

def setup_inputs():

    _w = (lambda a: (lambda t: t.to(torch.bfloat16) if t.is_floating_point() else t)(torch.as_tensor(a)))
    def _A_setup():
        B, Sq, D = 16, 144, 512
        H, Sk, Dh = 32, 512, 128
        return {
            "x": _w((lambda *s: torch.randn(*s, dtype=torch.bfloat16) * 0.8)(B, Sq, D)),
            "k_cache": _w((lambda *s: torch.randn(*s, dtype=torch.bfloat16) * 0.8)(B, H, Sk, Dh)),
            "v_cache": _w((lambda *s: torch.randn(*s, dtype=torch.bfloat16) * 0.05)(B, H, Sk, Dh)),
            "wq": _w((lambda *s: torch.randn(*s, dtype=torch.bfloat16) * 0.8)(D, H * Dh) * (D ** -0.5)),
            "wo": _w((lambda *s: torch.randn(*s, dtype=torch.bfloat16) * 0.05)(H * Dh, D) * ((H * Dh) ** -0.5)),
        }
    _A_in = _A_setup()

    def _B_setup():
        B, Sq, D = 16, 144, 512
        H, Sk, Dh = 32, 512, 128
        return {
            "x": _w((lambda *s: torch.randn(*s, dtype=torch.bfloat16) * 0.8)(B, Sq, D)),
            "k_cache": _w((lambda *s: torch.randn(*s, dtype=torch.bfloat16) * 0.8)(B, H, Sk, Dh)),
            "v_cache": _w((lambda *s: torch.randn(*s, dtype=torch.bfloat16) * 0.05)(B, H, Sk, Dh)),
            "wq": _w((lambda *s: torch.randn(*s, dtype=torch.bfloat16) * 0.8)(D, H * Dh) * (D ** -0.5)),
            "wo": _w((lambda *s: torch.randn(*s, dtype=torch.bfloat16) * 0.05)(H * Dh, D) * ((H * Dh) ** -0.5)),
        }
    _B_in = _B_setup()

    return {
        "A_x": _A_in["x"],
        "A_k_cache": _A_in["k_cache"],
        "A_v_cache": _A_in["v_cache"],
        "A_wq": _A_in["wq"],
        "A_wo": _A_in["wo"],
        "B_x": _B_in["x"],
        "B_k_cache": _B_in["k_cache"],
        "B_v_cache": _B_in["v_cache"],
        "B_wq": _B_in["wq"],
        "B_wo": _B_in["wo"],
    }

def reference(A_x, A_k_cache, A_v_cache, A_wq, A_wo, B_x, B_k_cache, B_v_cache, B_wq, B_wo):
    def _A_ref(x, k_cache, v_cache, wq, wo):
        B, Sq, D = x.shape
        H, Dh = 32, 128
        q = (lambda x, *d: x.permute(*d))((x @ wq).reshape(B, Sq, H, Dh), 0, 2, 1, 3)
        scores = torch.einsum("bhqd,bhkd->bhqk", q, k_cache) * (Dh ** -0.5)
        p = _softmax(scores, axis=-1)
        o = torch.einsum("bhqk,bhkd->bhqd", p, v_cache)
        return (lambda x, *d: x.permute(*d))(o, 0, 2, 1, 3).reshape(B, Sq, H * Dh) @ wo

    def _B_ref(x, k_cache, v_cache, wq, wo):
        B, Sq, D = x.shape
        H, Dh = 32, 128
        q = (lambda x, *d: x.permute(*d))((x @ wq).reshape(B, Sq, H, Dh), 0, 2, 1, 3)
        scores = torch.einsum("bhqd,bhkd->bhqk", q, k_cache) * (Dh ** -0.5)
        p = _softmax(scores, axis=-1)
        o = torch.einsum("bhqk,bhkd->bhqd", p, v_cache)
        return (lambda x, *d: x.permute(*d))(o, 0, 2, 1, 3).reshape(B, Sq, H * Dh) @ wo

    a = _A_ref(A_x, A_k_cache, A_v_cache, A_wq, A_wo)
    b = _B_ref(B_x, B_k_cache, B_v_cache, B_wq, B_wo)
    return torch.concatenate([a, b], axis=-1)
```

```cpp
#include <cuda_runtime.h>
#include <cuda_bf16.h>
#include <cuda.h>
#include <stdint.h>
#include <string.h>

namespace {

constexpr int NPAIRS = 66;
constexpr int MAXT = 8;
constexpr int NA = 6;
constexpr int NB = 3;
#define ORING_N 2
constexpr int ORING = ORING_N;
constexpr uint32_t A_BYTES = 16384, B_BYTES = 18432, Q_BYTES = 36864;
constexpr uint32_t OFF_A = 0;
constexpr uint32_t OFF_B = OFF_A + NA * A_BYTES;
constexpr uint32_t OFF_Q = OFF_B + NB * B_BYTES;
constexpr uint32_t OFF_BAR = OFF_Q + 2 * Q_BYTES;
constexpr uint32_t OFF_L = OFF_BAR + 512;
constexpr uint32_t SMEM_BYTES = OFF_L + 4608;
constexpr int BAR_AE = 0;
constexpr int BAR_AP = BAR_AE + NA;
constexpr int BAR_BE = BAR_AP + NA;
constexpr int BAR_XD = BAR_BE + NB;
constexpr int BAR_G = BAR_XD + 2;
constexpr int BAR_WC = BAR_G + 8;
constexpr int BAR_KS = BAR_WC + 8;
constexpr int BAR_PV = BAR_KS + 8;
constexpr int BAR_QF = BAR_PV + 8;
constexpr int BAR_QE = BAR_QF + 2;
constexpr int BAR_OS = BAR_QE + 2;
constexpr int BAR_LF = BAR_OS + 2;
constexpr int BAR_OD = BAR_LF + 1;
constexpr int NBARS = BAR_OD + 1;
static_assert(NBARS * 8 <= 504 && OFF_BAR % 512 == 0, "barriers");
static_assert(SMEM_BYTES <= 232448, "smem");

#define PROMO_KV 0
#define PROMO_W 0
#define O_CHUNK 4608
#define PROF_AB0 24
#define PROF_C0 24
enum { T_Q1 = 0, T_Q2 = 1, T_OP = 2, T_OPH = 3 };

struct alignas(64) Params {
    CUtensorMap tmK[2], tmV[2], tmX[2], tmWq[2], tmWo[2], tmOut;
    const __nv_bfloat16* K[2];
    const __nv_bfloat16* V[2];
    uint16_t tasks[NPAIRS][MAXT];
    uint16_t oplist[2][8][32];
    uint16_t delay[NPAIRS];
    uint8_t ntasks[NPAIRS];
    int kv_window;
};

__device__ __align__(1024) uint8_t g_O[ORING][2 * NPAIRS][Q_BYTES];
__device__ unsigned g_oready[2 * NPAIRS][8];
__device__ __align__(16) unsigned g_ofree[2 * NPAIRS][ORING][4];
__device__ unsigned g_epoch;
__device__ unsigned g_done;
#define PROF(role, idx) do { } while (0)
#define PROFD(role) do { } while (0)
#define PROFEND(role) do { } while (0)
#define PROFG(role) do { } while (0)

__device__ __forceinline__ uint32_t smem_u32(const void* p) { return (uint32_t)__cvta_generic_to_shared(p); }
__device__ __forceinline__ void mbar_init(uint32_t bar, uint32_t cnt) { asm volatile("mbarrier.init.shared::cta.b64 [%0], %1;" ::"r"(bar), "r"(cnt) : "memory"); }
__device__ __forceinline__ void mbar_expect_tx(uint32_t bar, uint32_t bytes) { asm volatile("mbarrier.arrive.expect_tx.shared::cta.b64 _, [%0], %1;" ::"r"(bar), "r"(bytes) : "memory"); }
__device__ __forceinline__ void mbar_arrive(uint32_t bar, uint32_t cnt) { asm volatile("mbarrier.arrive.shared::cta.b64 _, [%0], %1;" ::"r"(bar), "r"(cnt) : "memory"); }
__device__ __forceinline__ void mbar_arrive_cluster(uint32_t cbar, uint32_t cnt) { asm volatile("mbarrier.arrive.shared::cluster.b64 _, [%0], %1;" ::"r"(cbar), "r"(cnt) : "memory"); }
__device__ __forceinline__ uint32_t mapa(uint32_t addr, uint32_t cta) { uint32_t r; asm("mapa.shared::cluster.u32 %0, %1, %2;" : "=r"(r) : "r"(addr), "r"(cta)); return r; }
__device__ __forceinline__ bool mbar_try(uint32_t bar, uint32_t parity) {
    uint32_t ok;
    asm volatile("{\n.reg .pred p;\nmbarrier.try_wait.parity.shared::cta.b64 p, [%1], %2;\nselp.u32 %0, 1, 0, p;\n}" : "=r"(ok) : "r"(bar), "r"(parity) : "memory");
    return ok != 0;
}
__device__ __forceinline__ bool mbar_test(uint32_t bar, uint32_t parity) {
    uint32_t ok;
    asm volatile("{\n.reg .pred p;\nmbarrier.test_wait.parity.shared::cta.b64 p, [%1], %2;\nselp.u32 %0, 1, 0, p;\n}" : "=r"(ok) : "r"(bar), "r"(parity) : "memory");
    return ok != 0;
}
__device__ __forceinline__ bool mbar_test2(uint32_t bar0, uint32_t par0, uint32_t bar1, uint32_t par1) {
    uint32_t ok;
    asm volatile("{\n.reg .pred p, q;\nmbarrier.test_wait.parity.shared::cta.b64 p, [%1], %2;\nmbarrier.test_wait.parity.shared::cta.b64 q, [%3], %4;\n"
                 "and.pred p, p, q;\nselp.u32 %0, 1, 0, p;\n}" : "=r"(ok) : "r"(bar0), "r"(par0), "r"(bar1), "r"(par1) : "memory");
    return ok != 0;
}
__device__ __forceinline__ uint32_t timer_hi() { uint64_t t; asm volatile("mov.u64 %0, %globaltimer;" : "=l"(t)); return (uint32_t)(t >> 30); }
__device__ __forceinline__ bool give_up(uint32_t bar, uint32_t t0) {
    const uint32_t fa = bar | 0x1FCu;
    uint32_t f;
    asm volatile("ld.volatile.shared.u32 %0, [%1];" : "=r"(f) : "r"(fa) : "memory");
    if (f == 0 && timer_hi() - t0 <= 2u) return false;
    asm volatile("st.volatile.shared.u32 [%0], %1;" ::"r"(fa), "r"(1u) : "memory");
    return true;
}
__device__ __forceinline__ void mbar_wait(uint32_t bar, uint32_t parity) {
    if (mbar_try(bar, parity)) return;
    const uint32_t t0 = timer_hi();
    while (!mbar_try(bar, parity)) { if (give_up(bar, t0)) break; }
}
__device__ __forceinline__ void named_sync(int id) { asm volatile("bar.sync %0, 128;" ::"r"(id) : "memory"); }
__device__ __forceinline__ void fence_async_smem() { asm volatile("fence.proxy.async.shared::cta;" ::: "memory"); }
__device__ __forceinline__ void wg_fence() { asm volatile("wgmma.fence.sync.aligned;" ::: "memory"); }
__device__ __forceinline__ void wg_commit() { asm volatile("wgmma.commit_group.sync.aligned;" ::: "memory"); }
template <int N> __device__ __forceinline__ void wg_wait() { asm volatile("wgmma.wait_group.sync.aligned %0;" ::"n"(N) : "memory"); }
__device__ __forceinline__ void touch(float (&d)[72]) {
#pragma unroll
    for (int i = 0; i < 72; i++) asm volatile("" : "+f"(d[i])::"memory");
}
__device__ __forceinline__ void fresh(float (&d)[72]) {
#pragma unroll
    for (int i = 0; i < 72; i++) d[i] = 0.f;
}
__device__ __forceinline__ uint64_t mkdesc(uint32_t addr) { return (uint64_t)(((addr & 0x3FFFF) >> 4) | (1u << 16)) | ((uint64_t)0x40000040u << 32); }

template <int TA> __device__ __forceinline__ void wgmma_n144(float (&d)[72], uint64_t da, uint64_t db, int scale_d) {
    asm volatile("{\n.reg .pred p;\nsetp.ne.b32 p, %74, 0;\n"
        "wgmma.mma_async.sync.aligned.m64n144k16.f32.bf16.bf16 "
        "{%0, %1, %2, %3, %4, %5, %6, %7, %8, %9, %10, %11, "
        "%12, %13, %14, %15, %16, %17, %18, %19, %20, %21, %22, %23, "
        "%24, %25, %26, %27, %28, %29, %30, %31, %32, %33, %34, %35, "
        "%36, %37, %38, %39, %40, %41, %42, %43, %44, %45, %46, %47, "
        "%48, %49, %50, %51, %52, %53, %54, %55, %56, %57, %58, %59, "
        "%60, %61, %62, %63, %64, %65, %66, %67, %68, %69, %70, %71}, "
        "%72, %73, p, 1, 1, %75, 0;\n}\n"
        : "+f"(d[0]), "+f"(d[1]), "+f"(d[2]), "+f"(d[3]), "+f"(d[4]), "+f"(d[5]), "+f"(d[6]), "+f"(d[7]),
          "+f"(d[8]), "+f"(d[9]), "+f"(d[10]), "+f"(d[11]), "+f"(d[12]), "+f"(d[13]), "+f"(d[14]), "+f"(d[15]),
          "+f"(d[16]), "+f"(d[17]), "+f"(d[18]), "+f"(d[19]), "+f"(d[20]), "+f"(d[21]), "+f"(d[22]), "+f"(d[23]),
          "+f"(d[24]), "+f"(d[25]), "+f"(d[26]), "+f"(d[27]), "+f"(d[28]), "+f"(d[29]), "+f"(d[30]), "+f"(d[31]),
          "+f"(d[32]), "+f"(d[33]), "+f"(d[34]), "+f"(d[35]), "+f"(d[36]), "+f"(d[37]), "+f"(d[38]), "+f"(d[39]),
          "+f"(d[40]), "+f"(d[41]), "+f"(d[42]), "+f"(d[43]), "+f"(d[44]), "+f"(d[45]), "+f"(d[46]), "+f"(d[47]),
          "+f"(d[48]), "+f"(d[49]), "+f"(d[50]), "+f"(d[51]), "+f"(d[52]), "+f"(d[53]), "+f"(d[54]), "+f"(d[55]),
          "+f"(d[56]), "+f"(d[57]), "+f"(d[58]), "+f"(d[59]), "+f"(d[60]), "+f"(d[61]), "+f"(d[62]), "+f"(d[63]),
          "+f"(d[64]), "+f"(d[65]), "+f"(d[66]), "+f"(d[67]), "+f"(d[68]), "+f"(d[69]), "+f"(d[70]), "+f"(d[71])
        : "l"(da), "l"(db), "r"(scale_d), "n"(TA));
}

__device__ __forceinline__ uint32_t pack_bf16(float lo, float hi) { uint32_t r; asm("cvt.rn.bf16x2.f32 %0, %1, %2;" : "=r"(r) : "f"(hi), "f"(lo)); return r; }
__device__ __forceinline__ uint32_t max_bf16x2(uint32_t a, uint32_t b) { uint32_t r; asm("max.bf16x2 %0, %1, %2;" : "=r"(r) : "r"(a), "r"(b)); return r; }
__device__ __forceinline__ float ex2(float x) { float r; asm volatile("ex2.approx.ftz.f32 %0, %1;" : "=f"(r) : "f"(x)); return r; }
__device__ __forceinline__ void stsm_t(uint32_t addr, uint32_t r0, uint32_t r1, uint32_t r2, uint32_t r3) {
    asm volatile("stmatrix.sync.aligned.m8n8.x4.trans.shared.b16 [%0], {%1, %2, %3, %4};" ::"r"(addr), "r"(r0), "r"(r1), "r"(r2), "r"(r3) : "memory");
}
__device__ __forceinline__ float4 lds128f(uint32_t a) { float4 v; asm volatile("ld.shared.v4.f32 {%0, %1, %2, %3}, [%4];" : "=f"(v.x), "=f"(v.y), "=f"(v.z), "=f"(v.w) : "r"(a) : "memory"); return v; }
__device__ __forceinline__ uint4 lds128u(uint32_t a) { uint4 v; asm volatile("ld.shared.v4.u32 {%0, %1, %2, %3}, [%4];" : "=r"(v.x), "=r"(v.y), "=r"(v.z), "=r"(v.w) : "r"(a) : "memory"); return v; }
__device__ __forceinline__ float2 lds64f(uint32_t a) { float2 v; asm volatile("ld.shared.v2.f32 {%0, %1}, [%2];" : "=f"(v.x), "=f"(v.y) : "r"(a) : "memory"); return v; }
__device__ __forceinline__ float rcp(float x) { float r; asm("rcp.approx.ftz.f32 %0, %1;" : "=f"(r) : "f"(x)); return r; }
__device__ __forceinline__ float lds32f(uint32_t a) { float v; asm volatile("ld.shared.f32 %0, [%1];" : "=f"(v) : "r"(a) : "memory"); return v; }
__device__ __forceinline__ void sts32f(uint32_t a, float v) { asm volatile("st.shared.f32 [%0], %1;" ::"r"(a), "f"(v) : "memory"); }
__device__ __forceinline__ void sts128f(uint32_t a, float x, float y, float z, float w) { asm volatile("st.shared.v4.f32 [%0], {%1, %2, %3, %4};" ::"r"(a), "f"(x), "f"(y), "f"(z), "f"(w) : "memory"); }
__device__ __forceinline__ void sts128u(uint32_t a, uint32_t x, uint32_t y, uint32_t z, uint32_t w) { asm volatile("st.shared.v4.u32 [%0], {%1, %2, %3, %4};" ::"r"(a), "r"(x), "r"(y), "r"(z), "r"(w) : "memory"); }

__device__ __forceinline__ void tma3d(uint32_t dst, const CUtensorMap* tm, int c0, int c1, int c2, uint32_t bar, uint64_t pol) {
    asm volatile("cp.async.bulk.tensor.3d.shared::cluster.global.mbarrier::complete_tx::bytes.L2::cache_hint [%0], [%1, {%3, %4, %5}], [%2], %6;"
                 ::"r"(dst), "l"(tm), "r"(bar), "r"(c0), "r"(c1), "r"(c2), "l"(pol) : "memory");
}
__device__ __forceinline__ void tma2d(uint32_t dst, const CUtensorMap* tm, int c0, int c1, uint32_t bar) {
    asm volatile("cp.async.bulk.tensor.2d.shared::cluster.global.mbarrier::complete_tx::bytes [%0], [%1, {%3, %4}], [%2];"
                 ::"r"(dst), "l"(tm), "r"(bar), "r"(c0), "r"(c1) : "memory");
}
__device__ __forceinline__ void tma2d_mc(uint32_t dst, const CUtensorMap* tm, int c0, int c1, uint32_t bar) {
    asm volatile("cp.async.bulk.tensor.2d.shared::cluster.global.mbarrier::complete_tx::bytes.multicast::cluster [%0], [%1, {%3, %4}], [%2], %5;"
                 ::"r"(dst), "l"(tm), "r"(bar), "r"(c0), "r"(c1), "h"((uint16_t)3) : "memory");
}
__device__ __forceinline__ void tma2d_prefetch(const CUtensorMap* tm, int c0, int c1) {
    asm volatile("cp.async.bulk.prefetch.tensor.2d.L2.global [%0, {%1, %2}];" ::"l"(tm), "r"(c0), "r"(c1) : "memory");
}
__device__ __forceinline__ void tma2d_store(const CUtensorMap* tm, int c0, int c1, uint32_t src) {
    asm volatile("cp.async.bulk.tensor.2d.global.shared::cta.bulk_group [%0, {%2, %3}], [%1];" ::"l"(tm), "r"(src), "r"(c0), "r"(c1) : "memory");
}
__device__ __forceinline__ void bulk_g2s(uint32_t dst, const void* src, uint32_t bytes, uint32_t bar) {
    asm volatile("cp.async.bulk.shared::cluster.global.mbarrier::complete_tx::bytes [%0], [%1], %2, [%3];" ::"r"(dst), "l"(src), "r"(bytes), "r"(bar) : "memory");
}
__device__ __forceinline__ void bulk_s2g(void* dst, uint32_t src, uint32_t bytes) {
    asm volatile("cp.async.bulk.global.shared::cta.bulk_group [%0], [%1], %2;" ::"l"(dst), "r"(src), "r"(bytes) : "memory");
}
__device__ __forceinline__ void bulk_prefetch(const void* src, uint32_t bytes, uint64_t pol) {
    asm volatile("cp.async.bulk.prefetch.L2.global.L2::cache_hint [%0], %1, %2;" ::"l"(src), "r"(bytes), "l"(pol) : "memory");
}
__device__ __forceinline__ void bulk_commit() { asm volatile("cp.async.bulk.commit_group;" ::: "memory"); }
__device__ __forceinline__ void flag_wait(const unsigned* f, unsigned v, uint32_t bars) {
    unsigned x;
    const uint32_t t0 = timer_hi();
    while (true) {
        asm volatile("ld.acquire.gpu.global.u32 %0, [%1];" : "=r"(x) : "l"(f) : "memory");
        if ((int)(x - v) >= 0) break;
        __nanosleep(64);
        if (give_up(bars, t0)) break;
    }
}
__device__ __forceinline__ void flag_wait4(const unsigned* f, unsigned v, uint32_t bars) {
    const uint32_t t0 = timer_hi();
    while (true) {
        unsigned a, b, c, d;
        asm volatile("ld.relaxed.gpu.global.v4.u32 {%0, %1, %2, %3}, [%4];" : "=r"(a), "=r"(b), "=r"(c), "=r"(d) : "l"(f) : "memory");
        if ((int)((a - v) | (b - v) | (c - v) | (d - v)) >= 0) break;
        __nanosleep(64);
        if (give_up(bars, t0)) break;
    }
    asm volatile("fence.acq_rel.gpu;" ::: "memory");
}
__device__ __forceinline__ void cluster_sync_all() { asm volatile("barrier.cluster.arrive.aligned;\nbarrier.cluster.wait.aligned;" ::: "memory"); }

__device__ __forceinline__ uint32_t rel_addr(int lane, uint32_t cb0, uint32_t cb1, uint32_t other, uint32_t slot, bool next_mc) {
    const uint32_t addr = (lane == 2 ? cb1 : cb0) + 8 * (lane == 0 ? other : BAR_AE + slot);
    return lane < (next_mc ? 3 : 2) ? addr : 0u;
}
__device__ __forceinline__ void release(int lane, uint32_t addr, uint32_t cnt) {
    asm volatile("{\n.reg .pred p, q, r;\nsetp.ne.u32 r, %0, 0;\nsetp.eq.and.s32 q, %2, 2, r;\nsetp.ne.and.s32 p, %2, 2, r;\n"
                 "@q mbarrier.arrive.shared::cluster.b64 _, [%0], %1;\n@p mbarrier.arrive.shared::cta.b64 _, [%0], %1;\n}" ::"r"(addr), "r"(cnt), "r"(lane) : "memory");
}
__device__ __forceinline__ uint32_t wrap3(uint32_t s) { return s >= 3 ? s - 3 : s; }

template <int ACC> __device__ __forceinline__ void step_ab(float (&acc)[72], uint64_t da, uint64_t db, int lane, uint32_t raddr, uint32_t rcnt) {
    wg_fence();
    wgmma_n144<1>(acc, da, db, ACC);
    wgmma_n144<1>(acc, da + 128, db + 2, 1);
    if (ACC) { wg_commit(); wg_wait<1>(); release(lane, raddr, rcnt); wg_fence(); }
    wgmma_n144<1>(acc, da + 256, db + 4, 1);
    wgmma_n144<1>(acc, da + 384, db + 6, 1);
    wg_commit();
}
template <int ACC> __device__ __forceinline__ void step_c(float (&acc0)[72], float (&acc1)[72], uint64_t da, uint64_t db, int lane, uint32_t raddr, uint32_t rcnt) {
    wg_fence();
    wgmma_n144<1>(acc0, da, db, ACC);
    wgmma_n144<1>(acc1, da + 512, db, ACC);
    if (ACC) { wg_commit(); wg_wait<1>(); release(lane, raddr, rcnt); wg_fence(); }
#pragma unroll
    for (int kk = 1; kk < 4; kk++) {
        wgmma_n144<1>(acc0, da + kk * 128, db + kk * 2, 1);
        wgmma_n144<1>(acc1, da + 512 + kk * 128, db + kk * 2, 1);
    }
    wg_commit();
}
__device__ __forceinline__ void publish(uint32_t bar, int lane) {
    fence_async_smem();
    __syncwarp();
    if (lane == 0) mbar_arrive(bar, 1);
}
__device__ __forceinline__ void scale(float (&d)[72], float sc) {
#pragma unroll
    for (int i = 0; i < 72; i++) d[i] *= sc;
}
__device__ __forceinline__ void store_panel(const float (&d)[72], uint32_t lane_addr, float sc) {
#pragma unroll
    for (int jj = 0; jj < 9; jj++)
        stsm_t(lane_addr + jj * 2048, pack_bf16(d[8 * jj] * sc, d[8 * jj + 1] * sc), pack_bf16(d[8 * jj + 2] * sc, d[8 * jj + 3] * sc),
               pack_bf16(d[8 * jj + 4] * sc, d[8 * jj + 5] * sc), pack_bf16(d[8 * jj + 6] * sc, d[8 * jj + 7] * sc));
}

constexpr float L_MIN = 9.313225746154785e-10f, L_MAX = 1.125899906842624e15f;
constexpr float SM_SCALE = 0.08838834764831845f * 1.4426950408889634f;

template <int I0, int I1> __device__ __forceinline__ void exp_part(float (&d)[72]) {
#pragma unroll
    for (int i = 4 * I0; i < 4 * I1; i++) d[i] = ex2(d[i]);
}
template <int J0, int J1> __device__ __forceinline__ void out_part(const float (&d)[72], float (&sum)[36], uint32_t pa) {
#pragma unroll
    for (int jj = J0; jj < J1; jj++) {
        stsm_t(pa + jj * 2048, pack_bf16(d[8 * jj], d[8 * jj + 1]), pack_bf16(d[8 * jj + 2], d[8 * jj + 3]),
               pack_bf16(d[8 * jj + 4], d[8 * jj + 5]), pack_bf16(d[8 * jj + 6], d[8 * jj + 7]));
        sum[4 * jj] += d[8 * jj] + d[8 * jj + 2]; sum[4 * jj + 1] += d[8 * jj + 1] + d[8 * jj + 3];
        sum[4 * jj + 2] += d[8 * jj + 4] + d[8 * jj + 6]; sum[4 * jj + 3] += d[8 * jj + 5] + d[8 * jj + 7];
    }
}
__device__ __forceinline__ void reduce_sums(float (&sum)[36], uint32_t row, uint32_t bars, int lane) {
    const bool h4 = lane & 4, h8 = lane & 8, h16 = lane & 16;
    const uint32_t la = row + (lane & 3) * 144 + (h4 ? 72 : 0) + (h8 ? 36 : 0) + (h16 ? 20 : 0);
#pragma unroll
    for (int i = 0; i < 18; i++) { const float keep = h4 ? sum[18 + i] : sum[i], send = h4 ? sum[i] : sum[18 + i]; sum[i] = keep + __shfl_xor_sync(0xffffffffu, send, 4); }
#pragma unroll
    for (int i = 0; i < 9; i++) { const float keep = h8 ? sum[9 + i] : sum[i], send = h8 ? sum[i] : sum[9 + i]; sum[i] = keep + __shfl_xor_sync(0xffffffffu, send, 8); }
    const float mid = sum[4] + __shfl_xor_sync(0xffffffffu, sum[4], 16);
#pragma unroll
    for (int i = 0; i < 4; i++) { const float keep = h16 ? sum[5 + i] : sum[i], send = h16 ? sum[i] : sum[5 + i]; sts32f(la + i * 4, keep + __shfl_xor_sync(0xffffffffu, send, 16)); }
    if (!h16) sts32f(la + 16, mid);
    __syncwarp();
    if (lane == 0) mbar_arrive(bars + 8 * BAR_LF, 1);
#pragma unroll
    for (int i = 0; i < 36; i++) sum[i] = 0.f;
}
template <int ID> __device__ __forceinline__ void sched_fence(int opaque) { asm volatile("{\n.reg .pred p;\nsetp.eq.s32 p, %0, %1;\n@p exit;\n}" ::"r"(opaque), "n"(-77 - ID) : "memory"); }

__device__ __forceinline__ void slow_head(const __nv_bfloat16* __restrict__ Kg, const __nv_bfloat16* __restrict__ Vg, uint32_t qbuf, uint32_t scr, int tid) {
    const int lane = tid & 31, w = tid >> 5;
#pragma unroll 1
    for (int q = 0; q < 144; q++) {
        float s[4];
#pragma unroll
        for (int i = 0; i < 4; i++) {
            const uint4* kr = reinterpret_cast<const uint4*>(Kg + (size_t)(tid + 128 * i) * 128);
            float a = 0.f;
#pragma unroll 1
            for (int c = 0; c < 16; c++) {
                uint4 kv = kr[c];
                uint4 qv = lds128u(qbuf + (c >> 3) * B_BYTES + q * 128 + (((c & 7) ^ (q & 7)) << 4));
                a = fmaf(__uint_as_float(kv.x << 16), __uint_as_float(qv.x << 16), a); a = fmaf(__uint_as_float(kv.x & 0xffff0000u), __uint_as_float(qv.x & 0xffff0000u), a);
                a = fmaf(__uint_as_float(kv.y << 16), __uint_as_float(qv.y << 16), a); a = fmaf(__uint_as_float(kv.y & 0xffff0000u), __uint_as_float(qv.y & 0xffff0000u), a);
                a = fmaf(__uint_as_float(kv.z << 16), __uint_as_float(qv.z << 16), a); a = fmaf(__uint_as_float(kv.z & 0xffff0000u), __uint_as_float(qv.z & 0xffff0000u), a);
                a = fmaf(__uint_as_float(kv.w << 16), __uint_as_float(qv.w << 16), a); a = fmaf(__uint_as_float(kv.w & 0xffff0000u), __uint_as_float(qv.w & 0xffff0000u), a);
            }
            s[i] = a;
        }
        float m = fmaxf(fmaxf(s[0], s[1]), fmaxf(s[2], s[3]));
#pragma unroll
        for (int o = 16; o; o >>= 1) m = fmaxf(m, __shfl_xor_sync(0xffffffffu, m, o));
        if (lane == 0) sts32f(scr + 2048 + w * 4, m);
        named_sync(3);
        float4 mm = lds128f(scr + 2048);
        m = fmaxf(fmaxf(mm.x, mm.y), fmaxf(mm.z, mm.w));
        float l = 0.f;
#pragma unroll
        for (int i = 0; i < 4; i++) { float pv = exp2f(s[i] - m); l += pv; sts32f(scr + (tid + 128 * i) * 4, pv); }
#pragma unroll
        for (int o = 16; o; o >>= 1) l += __shfl_xor_sync(0xffffffffu, l, o);
        if (lane == 0) sts32f(scr + 2064 + w * 4, l);
        named_sync(3);
        float4 ll = lds128f(scr + 2064);
        l = (ll.x + ll.y) + (ll.z + ll.w);
        float o = 0.f;
#pragma unroll 4
        for (int k = 0; k < 512; k++) o = fmaf(lds32f(scr + k * 4), __bfloat162float(Vg[(size_t)k * 128 + tid]), o);
        uint32_t oa = qbuf + (tid >> 6) * B_BYTES + q * 128 + ((((tid & 63) >> 3) ^ (q & 7)) << 4) + (tid & 7) * 2;
        unsigned short ob = __bfloat16_as_ushort(__float2bfloat16(o / l));
        asm volatile("st.shared.u16 [%0], %1;" ::"r"(oa), "h"(ob) : "memory");
        named_sync(3);
    }
}

__global__ void __cluster_dims__(2, 1, 1) __launch_bounds__(512, 1) fused_mha_kernel(const __grid_constant__ Params p) {
    extern __shared__ __align__(1024) uint8_t smem_raw[];
    const uint32_t sb = smem_u32(smem_raw);
    const uint32_t bars = sb + OFF_BAR;
    const int wg = __shfl_sync(0xffffffffu, (int)(threadIdx.x >> 7), 0);
    const int warp = __shfl_sync(0xffffffffu, (int)((threadIdx.x >> 5) & 3), 0);
    const int lane = threadIdx.x & 31;
    const int cta = blockIdx.x, pair = cta >> 1;
    const uint32_t rank = cta & 1;
    const int ntasks = p.ntasks[pair];

    if (threadIdx.x < 64) {
        const int i = threadIdx.x;
        const uint32_t cnt = i < BAR_BE ? 8 : i < BAR_XD ? 24 : i < BAR_G ? 48 : i < BAR_WC ? 2 : i < BAR_KS ? 1 : i < BAR_QF ? 5 : i < BAR_QE ? 8 : i < BAR_OS ? 1
                           : i < BAR_LF ? 4 : i == BAR_LF ? 8 : 3;
        if (i < NBARS) mbar_init(bars + 8 * i, cnt);
        if (i == BAR_KS) mbar_arrive(bars + 8 * BAR_KS, 4);
        if (i == 63) asm volatile("st.shared.u32 [%0], %1;" ::"r"(bars + 0x1FC), "r"(0u) : "memory");
        asm volatile("fence.mbarrier_init.release.cluster;" ::: "memory");
    }
    const uint32_t tk0 = p.tasks[pair][0];
    __syncthreads();
    asm volatile("barrier.cluster.arrive.relaxed.aligned;" ::: "memory");
    if (wg == 3 && lane == 0 && (tk0 & 3) < T_OP) {
        const int br = (tk0 >> 2) & 1;
        if (warp == 1 || warp == 2) {
            const int row = (((tk0 >> 3) & 7) * 2 + rank) * 144;
#pragma unroll
            for (int i = 0; i < 2; i++) {
                const int k = warp == 2 ? i : 2 + i;
                tma2d(sb + (warp == 2 ? OFF_Q : OFF_B) + i * B_BYTES, &p.tmX[br], k * 64, row, bars + 8 * (BAR_G + k));
                mbar_expect_tx(bars + 8 * (BAR_G + k), B_BYTES);
            }
        } else if ((warp & 1) <= (int)(tk0 & 3)) {
            const int ring = warp & 1, c0 = ((tk0 >> 6) + ring) * 128;
#pragma unroll
            for (int i = 0; i < 3; i++) {
                const uint32_t bar = bars + 8 * (BAR_G + ring * 8 + i), dst = sb + OFF_A + (3 * ring + i) * A_BYTES;
                tma2d(dst, &p.tmWq[br], c0, i * 64, bar);
                tma2d(dst + 8192, &p.tmWq[br], c0 + 64, i * 64, bar);
                mbar_expect_tx(bar, A_BYTES);
            }
        }
    }
    __syncwarp();
    asm volatile("barrier.cluster.wait.aligned;" ::: "memory");

    if (wg == 3) {
        asm volatile("setmaxnreg.dec.sync.aligned.u32 40;");
        if (warp == 0 || warp == 3) {
            if (lane == 0) {
                const int ring = warp & 1;
                uint64_t pol;
                asm volatile("createpolicy.fractional.L2::evict_first.b64 %0, 1.0;" : "=l"(pol));
                uint32_t s = 3 * ring, ph = 1, ph_p = 0, used = 0;
                const unsigned t0 = (unsigned)clock();
                for (int t = 0; t < ntasks; t++) {
                    const uint32_t tk = p.tasks[pair][t];
                    const int type = tk & 3, br = (tk >> 2) & 1, bp = (tk >> 3) & 7, hh = tk >> 6;
                    const int nw = (ring == 1 && (type == T_Q1 || type == T_OPH)) ? 0 : type >= T_OP ? 64 : 8;
                    const CUtensorMap* tm = type >= T_OP ? &p.tmWo[br] : &p.tmWq[br];
                    const int c0 = (hh + ring) * 128 + rank * 64;
                    int i = 0;
                    if (t == 0 && nw == 8) { i = 3; ph ^= 1; used = 1; }
                    for (; i < nw; i++) {
                        const uint32_t bar = bars + 8 * (BAR_G + ring * 8 + (i & 7)), dst = sb + OFF_A + s * A_BYTES + rank * 8192;
                        const int c1 = type >= T_OP ? (p.oplist[br][bp][i >> 1] & 31) * 128 + (i & 1) * 64 : i * 64;
                        const uint32_t pp = ((ph_p >> s) & 1) ^ (used ^ 1);
                        if (!mbar_test2(bars + 8 * (BAR_AE + s), ph, bars + 8 * (BAR_AP + s), pp)) {
                            mbar_wait(bars + 8 * (BAR_AE + s), ph);
                            mbar_wait(bars + 8 * (BAR_AP + s), pp);
                        }
                        tma2d_mc(dst, tm, c0, c1, bar);
                        mbar_expect_tx(bar, A_BYTES);
                        ph_p ^= used << s;
                        if (++s == 3 * ring + 3) { s -= 3; ph ^= 1; used = 1; }
                    }
                    if (type >= T_OP) continue;
                    if (t == 0) { const unsigned d = p.delay[pair] * 64u; while ((unsigned)clock() - t0 < d) __nanosleep(100); }
                    const int row0 = ((bp * 2 + rank) * 32 + hh) * 512;
                    for (int g = 0; g < 8 * (type + 1); g++) {
                        const uint32_t bar = bars + 8 * (BAR_KS + ring * 8 + (g & 7));
                        mbar_wait(bars + 8 * (BAR_AE + s), ph);
                        tma3d(sb + OFF_A + s * A_BYTES, ring ? &p.tmV[br] : &p.tmK[br], 0, row0 + g * 64, 0, bar, pol);
                        mbar_expect_tx(bar, A_BYTES);
                        if (++s == 3 * ring + 3) { s -= 3; ph ^= 1; used = 1; }
                    }
                }
            }
        } else if (warp == 1) {
            if (lane == 0) {
                uint32_t s = 0, ph = 1;
                for (int t = 0; t < ntasks; t++) {
                    const uint32_t tk = p.tasks[pair][t];
                    const int type = tk & 3, br = (tk >> 2) & 1, bp = (tk >> 3) & 7;
                    if (type >= T_OP) {
                        const unsigned base = *(volatile unsigned*)&g_epoch * 16u;
                        for (int i = 0; i < 64; i++) {
                            const uint32_t e = p.oplist[br][bp][i >> 1];
                            const int src = ((e >> 5) & 127) * 2 + rank, seq = e >> 12;
                            if ((i & 1) == 0) { flag_wait(&g_oready[src][0], base + seq + 1, bars); asm volatile("fence.proxy.async.global;" ::: "memory"); }
                            mbar_wait(bars + 8 * (BAR_BE + s), ph);
                            bulk_g2s(sb + OFF_B + s * B_BYTES, &g_O[seq % ORING][src][(i & 1) * B_BYTES], B_BYTES, bars + 8 * (BAR_G + (i & 7)));
                            mbar_expect_tx(bars + 8 * (BAR_G + (i & 7)), B_BYTES);
                            if (++s == NB) { s = 0; ph ^= 1; }
                        }
                    } else {
                        if (t == 0) s = 2;
                        for (int ii = t == 0 ? 4 : 2; ii < 6; ii++) {
                            const int i = ii == 5 ? 7 : ii;
                            mbar_wait(bars + 8 * (BAR_BE + s), ph);
                            tma2d(sb + OFF_B + s * B_BYTES, &p.tmX[br], i * 64, (bp * 2 + rank) * 144, bars + 8 * (BAR_G + i));
                            mbar_expect_tx(bars + 8 * (BAR_G + i), B_BYTES);
                            if (++s == NB) { s = 0; ph ^= 1; }
                        }
                        for (int i = 0; i < 8 * (type + 1); i++) {
                            mbar_wait(bars + 8 * (BAR_BE + s), ph);
                            if (++s == NB) { s = 0; ph ^= 1; }
                        }
                    }
                }
            }
        } else {
            if (lane == 0) {
                int natt = 0, nq = 0, nop = 0;
                bool have01 = false;
                for (int t = 0; t < ntasks; t++) {
                    const uint32_t tk = p.tasks[pair][t];
                    const int type = tk & 3;
                    if (type >= T_OP) { mbar_wait(bars + 8 * BAR_OD, nop & 1); nop++; continue; }
                    const uint32_t nk = t + 1 < ntasks ? p.tasks[pair][t + 1] : (uint32_t)T_OP;
                    auto load_x = [&](uint32_t task, int buf, int panel, int k) {
                        const uint32_t bar = bars + 8 * (BAR_G + k);
                        tma2d(sb + OFF_Q + buf * Q_BYTES + panel * B_BYTES, &p.tmX[(task >> 2) & 1], k * 64, (((task >> 3) & 7) * 2 + rank) * 144, bar);
                        mbar_expect_tx(bar, B_BYTES);
                    };
                    if (!have01) {
                        if (t != 0) { load_x(tk, natt & 1, 0, 0); load_x(tk, natt & 1, 1, 1); }
                        else mbar_wait(bars + 8 * BAR_G, 0);
                        load_x(tk, (natt + 1) & 1, 0, 5); load_x(tk, (natt + 1) & 1, 1, 6);
                    }
                    const unsigned base = *(volatile unsigned*)&g_epoch * 16u;
                    have01 = (nk & 3) < T_OP;
                    if (type == T_Q1) {
                        mbar_wait(bars + 8 * (BAR_XD + 1), nq & 1);
                        if (have01) { load_x(nk, (natt + 1) & 1, 0, 0); load_x(nk, (natt + 1) & 1, 1, 1); }
                    }
                    for (int e = 0; e <= type; e++, natt++) {
                        const int buf = natt & 1, slot = natt % ORING;
                        if (natt >= ORING) {
                            flag_wait4(&g_ofree[cta][slot][0], base + natt - ORING + 1, bars);
                            asm volatile("fence.proxy.async.global;" ::: "memory");
                        }
                        mbar_wait(bars + 8 * (BAR_OS + buf), (natt >> 1) & 1);
                        for (int panel = 0; panel < 2; panel++) {
                            for (uint32_t o = panel * B_BYTES; o < (panel + 1) * B_BYTES; o += O_CHUNK) {
                                bulk_s2g(&g_O[slot][cta][o], sb + OFF_Q + buf * Q_BYTES + o, O_CHUNK);
                                bulk_commit();
                                asm volatile("cp.async.bulk.wait_group.read 0;" ::: "memory");
                            }
                            if (have01) load_x(nk, buf, panel, (e == type ? 5 : 0) + panel);
                        }
                        mbar_arrive(bars + 8 * (BAR_QE + buf), 1);
                        asm volatile("cp.async.bulk.wait_group 0;" ::: "memory");
                        asm volatile("fence.proxy.async.global;" ::: "memory");
                        asm volatile("st.release.gpu.global.u32 [%0], %1;" ::"l"(&g_oready[cta][0]), "r"(base + natt + 1) : "memory");
                    }
                    nq++;
                }
            }
        }
        __syncwarp();
        cluster_sync_all();
        if (threadIdx.x == 384) {
            __threadfence();
            if (atomicAdd(&g_done, 1u) == gridDim.x - 1) { g_done = 0; __threadfence(); atomicAdd(&g_epoch, 1u); }
        }
    } else if (wg < 2) {
        asm volatile("setmaxnreg.inc.sync.aligned.u32 144;");
        float acc[72], sum[36];
        fresh(acc);
#pragma unroll
        for (int i = 0; i < 36; i++) sum[i] = 0.f;
        uint32_t as = 0, bslot = 0, bph = 1;
        uint32_t gph = 0, pend_bar = 0;
        int natt = 0, nq = 0;
        int opaque;
        asm volatile("ld.volatile.shared.u32 %0, [%1];" : "=r"(opaque) : "r"(bars + 0x1FC));
        opaque = __shfl_sync(0xffffffffu, opaque, 0);
        const uint32_t cb0 = bars, cb1 = mapa(bars, rank ^ 1) + 8 * NA;
        const uint32_t lane_off = ((lane >> 4) * 8 + (lane & 7)) * 128 + (((2 * warp + ((lane >> 3) & 1)) ^ (lane & 7)) << 4);
        const uint32_t lrow = sb + OFF_L + (wg * 4 + warp) * 576;
        int pidx = 0, didx = PROF_AB0;
        for (int t = 0; t < ntasks; t++) {
            const uint32_t tk = p.tasks[pair][t];
            const int type = tk & 3;
            uint32_t raddr = 0;
            const uint32_t rcnt = lane == 0 ? (type == T_Q1 || type == T_OPH ? 3 : 2) : 1;
            PROF(wg, pidx++);
            if (type >= T_OP) {
                if (pend_bar != 0) { publish(pend_bar, lane); reduce_sums(sum, lrow, bars, lane); pend_bar = 0; }
                const int br = (tk >> 2) & 1, bp = (tk >> 3) & 7, cq = tk >> 6;
                const unsigned base = *(volatile unsigned*)&g_epoch * 16u;
                fresh(acc);
#pragma unroll 1
                for (int k = 0; k < 64; k++) {
                    const uint32_t gbar = bars + 8 * (BAR_G + (k & 7)), par = (gph ^ (k >> 3)) & 1;
                    if (!mbar_test(gbar, par)) {
                        wg_wait<0>();
                        release(lane, raddr, rcnt);
                        raddr = 0;
                        mbar_wait(gbar, par);
                    }
                    const uint64_t da = mkdesc(sb + OFF_A + as * A_BYTES + wg * 8192), db = mkdesc(sb + OFF_B + bslot * B_BYTES);
                    step_ab<1>(acc, da, db, lane, raddr, rcnt);
                    raddr = rel_addr(lane, cb0, cb1, BAR_BE + bslot, as, true);
                    if ((k & 1) && threadIdx.x <= (type == T_OP ? 1u : 0u)) {
                        const uint32_t e = p.oplist[br][bp][k >> 1];
                        const int src = ((e >> 5) & 127) * 2 + rank, seq = e >> 12;
                        asm volatile("st.relaxed.gpu.global.u32 [%0], %1;" ::"l"(&g_ofree[src][seq % ORING][cq + threadIdx.x]), "r"(base + seq + 1) : "memory");
                    }
                    as = wrap3(as + 1);
                    if (++bslot == NB) { bslot = 0; bph ^= 1; }
                }
                wg_wait<0>();
                touch(acc);
                release(lane, raddr, rcnt);
                PROF(wg, pidx++);
                if (natt >= 1) mbar_wait(bars + 8 * (BAR_QE + ((natt - 1) & 1)), ((natt - 1) >> 1) & 1);
                if (natt >= 2) mbar_wait(bars + 8 * (BAR_QE + (natt & 1)), ((natt - 2) >> 1) & 1);
                store_panel(acc, sb + OFF_Q + wg * B_BYTES + lane_off, 1.0f);
                fence_async_smem();
                named_sync(1 + wg);
                if ((threadIdx.x & 127) == 0) {
                    tma2d_store(&p.tmOut, br * 512 + cq * 128 + wg * 64, (bp * 2 + rank) * 144, sb + OFF_Q + wg * B_BYTES);
                    bulk_commit();
                    asm volatile("cp.async.bulk.wait_group 0;" ::: "memory");
                    mbar_arrive(bars + 8 * BAR_OD, 1);
                }
                named_sync(1 + wg);
                continue;
            }
            {
                const uint32_t q0 = sb + OFF_Q + (natt & 1) * Q_BYTES, q1 = sb + OFF_Q + ((natt + 1) & 1) * Q_BYTES;
                bool red = pend_bar != 0;
#pragma unroll
                for (int k = 0; k < 8; k++) {
                    if (!mbar_test(bars + 8 * (BAR_G + k), gph)) {
                        wg_wait<0>();
                        release(lane, raddr, rcnt);
                        raddr = 0;
                        if (k == 0 && pend_bar != 0) publish(pend_bar, lane);
                        if (k == 0) pend_bar = 0;
                        if (k < 2 && red) reduce_sums(sum, lrow, bars, lane);
                        if (k < 2) red = false;
                        mbar_wait(bars + 8 * (BAR_G + k), gph);
                    }
                    PROFG(wg);
                    const uint64_t da = mkdesc(sb + OFF_A + as * A_BYTES + wg * 8192);
                    const uint64_t db = mkdesc(k < 2 ? q0 + k * B_BYTES : (k == 5 || k == 6) ? q1 + (k - 5) * B_BYTES : sb + OFF_B + bslot * B_BYTES);
                    if (k == 0) step_ab<0>(acc, da, db, lane, 0, 0); else step_ab<1>(acc, da, db, lane, raddr, rcnt);
                    if (k == 0 && pend_bar != 0) publish(pend_bar, lane);
                    if (k == 1 && red) reduce_sums(sum, lrow, bars, lane);
                    raddr = rel_addr(lane, cb0, cb1, k < 2 ? BAR_XD : (k == 5 || k == 6) ? BAR_XD + 1 : BAR_BE + bslot, as, k + 3 < 8);
                    as = wrap3(as + 1);
                    if (k >= 2 && k != 5 && k != 6) { if (++bslot == NB) { bslot = 0; bph ^= 1; } }
                }
                pend_bar = 0;
                const bool xd = mbar_test(bars + 8 * BAR_XD, nq & 1);
                wg_wait<0>();
                touch(acc);
                release(lane, raddr, rcnt);
                PROF(wg, pidx++);
                if (!xd) mbar_wait(bars + 8 * BAR_XD, nq & 1);
                store_panel(acc, q0 + wg * B_BYTES + lane_off, SM_SCALE);
                publish(bars + 8 * (BAR_QF + (natt & 1)), lane);
                nq++;
                gph ^= 1;
            }
            uint32_t ps = bslot + wg, pph = bph;
            if (ps >= NB) { ps -= NB; pph ^= 1; }
            const int ntile = 4 * (type + 1);
            uint32_t ks = wrap3(as + wg);
            bool ready = false;
            uint64_t da = mkdesc(sb + OFF_A + ks * A_BYTES), dq = mkdesc(sb + OFF_Q + (natt & 1) * Q_BYTES);
            mbar_wait(bars + 8 * (BAR_QF + (natt & 1)), (natt >> 1) & 1);
#pragma unroll 1
            for (int it = 0; it < ntile; it++) {
                const int tt = it & 3;
                const int j = 2 * tt + wg;
                bool red = it == 4;
                if (!ready) {
                    if (pend_bar != 0) publish(pend_bar, lane);
                    pend_bar = 0;
                    if (red) reduce_sums(sum, lrow, bars, lane);
                    red = false;
                    mbar_wait(bars + 8 * (BAR_KS + j), natt & 1);
                }
                PROFD(wg);
                wg_fence();
#pragma unroll
                for (int kk = 0; kk < 8; kk++) wgmma_n144<0>(acc, da + (kk >> 2) * 512 + (kk & 3) * 2, dq + (kk >> 2) * (B_BYTES >> 4) + (kk & 3) * 2, kk != 0);
                wg_commit();
                if (lane == 0) mbar_arrive(bars + 8 * (BAR_KS + ((j + 1) & 7)), 1);
                fence_async_smem();
                __syncwarp();
                if (pend_bar != 0 && lane == 0) mbar_arrive(pend_bar, 1);
                if (red) reduce_sums(sum, lrow, bars, lane);
                uint32_t ra = rel_addr(lane, cb0, cb1, 0, ks, 2 * it + wg + 3 >= 2 * ntile);
                if (lane == 0) ra = 0;
                uint32_t pa = sb + OFF_B + ps * B_BYTES + lane_off;
                const bool pfree = mbar_test(bars + 8 * (BAR_BE + ps), pph);
                asm volatile("" : "+r"(ra), "+r"(pa));
                wg_wait<0>();
                touch(acc);
                PROFD(wg);
                exp_part<0, 1>(acc);
                release(lane, ra, 2);
                exp_part<1, 6>(acc);
                if (!pfree) mbar_wait(bars + 8 * (BAR_BE + ps), pph);
                exp_part<6, 10>(acc); out_part<0, 2>(acc, sum, pa); sched_fence<0>(opaque);
                pend_bar = bars + 8 * (BAR_PV + j);
                ks = wrap3(ks + 2);
                ps += 2; if (ps >= NB) { ps -= NB; pph ^= 1; }
                if (tt == 3) natt++;
                da = mkdesc(sb + OFF_A + ks * A_BYTES); dq = mkdesc(sb + OFF_Q + (natt & 1) * Q_BYTES);
                exp_part<10, 14>(acc); out_part<2, 4>(acc, sum, pa); sched_fence<1>(opaque);
                exp_part<14, 18>(acc); out_part<4, 6>(acc, sum, pa);
                ready = it + 1 < ntile && mbar_test(bars + 8 * (BAR_KS + ((j + 2) & 7)), natt & 1);
                sched_fence<2>(opaque);
                out_part<6, 9>(acc, sum, pa);
            }
            for (int e = 0; e <= type; e++) {
                as = wrap3(as + 2);
                bslot += 2; if (bslot >= NB) { bslot -= NB; bph ^= 1; }
            }
        }
        if (pend_bar != 0) { publish(pend_bar, lane); reduce_sums(sum, lrow, bars, lane); }
        PROFEND(wg);
        cluster_sync_all();
    } else {
        asm volatile("setmaxnreg.inc.sync.aligned.u32 184;");
        float acc0[72], acc1[72];
        uint32_t as = 3, bslot = 0;
        uint32_t gph = 0, wph = 0;
        int natt = 0, nq = 0, nop = 0;
        const uint32_t cb0 = bars, cb1 = mapa(bars, rank ^ 1) + 8 * NA;
        const uint32_t lane_off = ((lane >> 4) * 8 + (lane & 7)) * 128 + (((2 * warp + ((lane >> 3) & 1)) ^ (lane & 7)) << 4);
        const int tid = threadIdx.x & 127;
        int pidx = 0, didx = PROF_C0;
        fresh(acc0); fresh(acc1);
        for (int t = 0; t < ntasks; t++) {
            const uint32_t tk = p.tasks[pair][t];
            const int type = tk & 3, br = (tk >> 2) & 1, bp = (tk >> 3) & 7, hh = tk >> 6;
            int tn = t + 1;
            while (tn < ntasks && (p.tasks[pair][tn] & 3) == T_OPH) tn++;
            const bool next_w = tn < ntasks && (p.tasks[pair][tn] & 3) != T_Q1;
            PROF(2, pidx++);
            if (type == T_OPH) {
                if (tid == 0) mbar_arrive(bars + 8 * BAR_OD, 1);
                mbar_wait(bars + 8 * BAR_OD, nop & 1);
                nop++;
                bslot = wrap3(bslot + 1);
                PROF(2, pidx++);
                PROF(2, pidx++);
                continue;
            }
            if (type == T_OP) {
                uint32_t raddr = 0;
                nop++;
                fresh(acc0); fresh(acc1);
#pragma unroll 1
                for (int k = 0; k < 64; k++) {
                    const uint32_t gbar = bars + 8 * (BAR_G + (k & 7)), gp = (gph ^ (k >> 3)) & 1, wp = (wph ^ (k >> 3)) & 1;
                    if (!mbar_test2(gbar, gp, gbar + 64, wp)) {
                        wg_wait<0>();
                        release(lane, raddr, 2);
                        raddr = 0;
                        mbar_wait(gbar, gp);
                        mbar_wait(gbar + 64, wp);
                    }
                    const uint64_t da = mkdesc(sb + OFF_A + as * A_BYTES), db = mkdesc(sb + OFF_B + bslot * B_BYTES);
                    step_c<1>(acc0, acc1, da, db, lane, raddr, 2);
                    raddr = rel_addr(lane, cb0, cb1, BAR_BE + bslot, as, k + 3 < 64 || next_w);
                    if (++as == 6) as = 3;
                    bslot = wrap3(bslot + 1);
                }
                wg_wait<0>();
                touch(acc0); touch(acc1);
                release(lane, raddr, 2);
                PROF(2, pidx++);
                if (natt >= 1) mbar_wait(bars + 8 * (BAR_QE + ((natt - 1) & 1)), ((natt - 1) >> 1) & 1);
                if (natt >= 2) mbar_wait(bars + 8 * (BAR_QE + (natt & 1)), ((natt - 2) >> 1) & 1);
                store_panel(acc0, sb + OFF_Q + 2 * B_BYTES + lane_off, 1.0f);
                store_panel(acc1, sb + OFF_Q + 3 * B_BYTES + lane_off, 1.0f);
                fence_async_smem();
                named_sync(3);
                if (tid == 0) {
                    tma2d_store(&p.tmOut, br * 512 + hh * 128 + 128, (bp * 2 + rank) * 144, sb + OFF_Q + 2 * B_BYTES);
                    tma2d_store(&p.tmOut, br * 512 + hh * 128 + 192, (bp * 2 + rank) * 144, sb + OFF_Q + 3 * B_BYTES);
                    bulk_commit();
                    asm volatile("cp.async.bulk.wait_group 0;" ::: "memory");
                    mbar_arrive(bars + 8 * BAR_OD, 1);
                }
                named_sync(3);
                PROF(2, pidx++);
                continue;
            }
            if (type == T_Q1) {
                bslot = wrap3(bslot + 1);
            } else {
                const uint32_t q0 = sb + OFF_Q + (natt & 1) * Q_BYTES, q1 = sb + OFF_Q + ((natt + 1) & 1) * Q_BYTES;
                uint32_t raddr = 0;
#pragma unroll
                for (int k = 0; k < 8; k++) {
                    if (!mbar_test2(bars + 8 * (BAR_G + k), gph, bars + 8 * (BAR_WC + k), wph)) {
                        wg_wait<0>();
                        release(lane, raddr, 2);
                        raddr = 0;
                        mbar_wait(bars + 8 * (BAR_G + k), gph);
                        mbar_wait(bars + 8 * (BAR_WC + k), wph);
                    }
                    PROFG(2);
                    const uint64_t da = mkdesc(sb + OFF_A + as * A_BYTES);
                    const uint64_t db = mkdesc(k < 2 ? q0 + k * B_BYTES : (k == 5 || k == 6) ? q1 + (k - 5) * B_BYTES : sb + OFF_B + bslot * B_BYTES);
                    if (k == 0) step_c<0>(acc0, acc1, da, db, lane, 0, 0); else step_c<1>(acc0, acc1, da, db, lane, raddr, 2);
                    raddr = rel_addr(lane, cb0, cb1, k < 2 ? BAR_XD : (k == 5 || k == 6) ? BAR_XD + 1 : BAR_BE + bslot, as, k + 3 < 8);
                    if (++as == 6) as = 3;
                    if (k >= 2 && k != 5 && k != 6) bslot = wrap3(bslot + 1);
                }
                wg_wait<0>();
                touch(acc0); touch(acc1);
                release(lane, raddr, 2);
                scale(acc0, SM_SCALE); scale(acc1, SM_SCALE);
                mbar_wait(bars + 8 * (BAR_XD + 1), nq & 1);
                store_panel(acc0, q1 + lane_off, 1.0f);
                store_panel(acc1, q1 + B_BYTES + lane_off, 1.0f);
                fence_async_smem();
                __syncwarp();
                if (lane == 0) mbar_arrive(bars + 8 * (BAR_QF + ((natt + 1) & 1)), 2);
                wph ^= 1;
            }
            nq++;
            gph ^= 1;
            PROF(2, pidx++);
#pragma unroll 1
            for (int e = 0; e <= type; e++, natt++) {
                const int buf = natt & 1;
                uint32_t raddr;
                const uint32_t rcnt = lane == 0 ? 6 : 2;
                {
                    mbar_wait(bars + 8 * BAR_PV, natt & 1);
                    PROFD(2);
                    const uint64_t da = mkdesc(sb + OFF_A + as * A_BYTES), db = mkdesc(sb + OFF_B + bslot * B_BYTES);
                    step_c<0>(acc0, acc1, da, db, lane, 0, 0);
                    raddr = rel_addr(lane, cb0, cb1, BAR_BE + bslot, as, false);
                    PROFD(2);
                    if (++as == 6) as = 3;
                    bslot = wrap3(bslot + 1);
                }
#pragma unroll 1
                for (int j = 1; j < 8; j++) {
                    if (!mbar_test(bars + 8 * (BAR_PV + j), natt & 1)) {
                        wg_wait<0>();
                        release(lane, raddr, rcnt);
                        raddr = 0;
                        mbar_wait(bars + 8 * (BAR_PV + j), natt & 1);
                    }
                    PROFD(2);
                    const uint64_t da = mkdesc(sb + OFF_A + as * A_BYTES), db = mkdesc(sb + OFF_B + bslot * B_BYTES);
                    step_c<1>(acc0, acc1, da, db, lane, raddr, rcnt);
                    raddr = rel_addr(lane, cb0, cb1, BAR_BE + bslot, as, next_w && e == type && j >= 5);
                    PROFD(2);
                    if (++as == 6) as = 3;
                    bslot = wrap3(bslot + 1);
                }
                mbar_wait(bars + 8 * BAR_LF, natt & 1);
                PROFD(2);
                bool bad = false;
                if (tid < 72) {
                    const uint32_t a = sb + OFF_L + tid * 8;
                    float2 v[8];
#pragma unroll
                    for (int r = 0; r < 8; r++) v[r] = lds64f(a + r * 576);
                    const float l0 = ((v[0].x + v[1].x) + (v[2].x + v[3].x)) + ((v[4].x + v[5].x) + (v[6].x + v[7].x));
                    const float l1 = ((v[0].y + v[1].y) + (v[2].y + v[3].y)) + ((v[4].y + v[5].y) + (v[6].y + v[7].y));
                    bad = !(l0 >= L_MIN && l0 <= L_MAX && l1 >= L_MIN && l1 <= L_MAX);
                    asm volatile("st.shared.v2.f32 [%0], {%1, %2};" ::"r"(a), "f"(rcp(l0)), "f"(rcp(l1)) : "memory");
                }
                uint32_t anybad;
                asm volatile("{\n.reg .pred p, q;\nsetp.ne.u32 p, %1, 0;\nbar.red.or.pred q, 3, 128, p;\nselp.u32 %0, 1, 0, q;\n}" : "=r"(anybad) : "r"((uint32_t)bad) : "memory");
                PROFD(2);
                const uint32_t ia = sb + OFF_L + (lane & 3) * 144;
                float4 nx0 = lds128f(ia), nx1 = lds128f(ia + 16);
                wg_wait<0>();
                touch(acc0); touch(acc1);
                release(lane, raddr, rcnt);
                const uint32_t qb = sb + OFF_Q + buf * Q_BYTES;
                if (anybad) {
                    const size_t hoff = (size_t)((bp * 2 + rank) * 32 + hh + e) * 512 * 128;
                    named_sync(3);
                    slow_head(p.K[br] + hoff, p.V[br] + hoff, qb, sb + OFF_L, tid);
                } else {
#pragma unroll
                    for (int jj = 0; jj < 9; jj++) {
                        const float4 iv = nx0;
                        nx0 = nx1;
                        if (jj + 2 < 9) nx1 = lds128f(ia + (jj + 2) * 16);
                        acc0[8 * jj] *= iv.x; acc0[8 * jj + 1] *= iv.y; acc0[8 * jj + 2] *= iv.x; acc0[8 * jj + 3] *= iv.y;
                        acc0[8 * jj + 4] *= iv.z; acc0[8 * jj + 5] *= iv.w; acc0[8 * jj + 6] *= iv.z; acc0[8 * jj + 7] *= iv.w;
                        acc1[8 * jj] *= iv.x; acc1[8 * jj + 1] *= iv.y; acc1[8 * jj + 2] *= iv.x; acc1[8 * jj + 3] *= iv.y;
                        acc1[8 * jj + 4] *= iv.z; acc1[8 * jj + 5] *= iv.w; acc1[8 * jj + 6] *= iv.z; acc1[8 * jj + 7] *= iv.w;
                    }
                    store_panel(acc0, qb + lane_off, 1.0f);
                    store_panel(acc1, qb + B_BYTES + lane_off, 1.0f);
                }
                publish(bars + 8 * (BAR_OS + buf), lane);
                PROFD(2);
                PROF(2, pidx++);
            }
        }
        PROFEND(2);
        cluster_sync_all();
    }
}

typedef CUresult (*EncodeFn)(CUtensorMap*, CUtensorMapDataType, cuuint32_t, void*, const cuuint64_t*, const cuuint64_t*, const cuuint32_t*, const cuuint32_t*,
                             CUtensorMapInterleave, CUtensorMapSwizzle, CUtensorMapL2promotion, CUtensorMapFloatOOBfill);

bool encode(EncodeFn fn, CUtensorMap* tm, const void* ptr, int rank, const cuuint64_t* dims, const cuuint64_t* strides, const cuuint32_t* box, int promo) {
    const cuuint32_t es[3] = {1, 1, 1};
    return fn(tm, CU_TENSOR_MAP_DATA_TYPE_BFLOAT16, rank, const_cast<void*>(ptr), dims, strides, box, es, CU_TENSOR_MAP_INTERLEAVE_NONE,
              CU_TENSOR_MAP_SWIZZLE_128B, (CUtensorMapL2promotion)promo, CU_TENSOR_MAP_FLOAT_OOB_FILL_NONE) == CUDA_SUCCESS;
}

struct Tune { int nX; float maxdelay; float stretch; int dbg; };

void build_schedule(Params& P, const Tune& tn) {
    const int NOP = 16, NATT = NPAIRS - NOP;
    double tm[NPAIRS], delay[NPAIRS];
    int left[NPAIRS], fs[NPAIRS], first[NPAIRS], seq[NPAIRS];
    struct Ev { double t; int pr, seq, br, bp, h; };
    static Ev evs[512];
    int nev = 0;
    const int nX = tn.nX, nY = NATT - nX;
    int ix = 0, iy = 0;
    for (int pr = 0; pr < NPAIRS; pr++) {
        tm[pr] = 0; delay[pr] = 0; fs[pr] = 0; first[pr] = 1; seq[pr] = 0; P.ntasks[pr] = 0; P.delay[pr] = 0;
        if (pr < NATT) {
            left[pr] = 10;
            const bool X = (ix * nY <= iy * nX && ix < nX) || iy >= nY;
            if (X) { fs[pr] = 1; delay[pr] = 1 + tn.maxdelay * ((ix * 7) % nX) / nX; ix++; }
            else { delay[pr] = 2 + tn.maxdelay * ((iy * 7) % nY) / nY; iy++; }
        } else left[pr] = (pr - NATT) < 12 ? 1 : 0;
    }
    int task = 0, pend = -1;
    while (true) {
        int pr = -1; double best = 0;
        for (int q = 0; q < NPAIRS; q++) if (left[q] > 0) {
            const int n = (left[q] == 1 || fs[q]) ? 1 : 2;
            double t = tm[q] + n; if (first[q] && delay[q] > t) t = delay[q];
            if (pr < 0 || t < best) { pr = q; best = t; }
        }
        if (pr < 0) break;
        const int n = (left[pr] == 1 || fs[pr]) ? 1 : 2; fs[pr] = 0;
        int tk, sub = 0;
        if (n == 1) { if (pend >= 0) { tk = pend; sub = 1; pend = -1; } else { tk = task++; pend = tk; } } else tk = task++;
        const int br = tk / 128, bp = tk % 8, h = ((tk % 128) / 8) * 2 + sub;
        P.tasks[pr][P.ntasks[pr]++] = (uint16_t)((n - 1) | (br << 2) | (bp << 3) | (h << 6));
        tm[pr] += n;
        if (first[pr] && delay[pr] > tm[pr]) { P.delay[pr] = (uint16_t)((delay[pr] * 4700 - 2000) / 64); tm[pr] = delay[pr]; }
        first[pr] = 0;
        for (int k = 0; k < n; k++) { tm[pr] += 2 * tn.stretch; evs[nev++] = {tm[pr], pr, seq[pr]++, br, bp, h + k}; }
        left[pr] -= n;
    }
    int cnt[2][8] = {};
    bool used[512] = {};
    for (int i = 0; i < nev; i++) {
        int b = -1;
        for (int k = 0; k < nev; k++) if (!used[k] && (b < 0 || evs[k].t < evs[b].t)) b = k;
        used[b] = true;
        const Ev& e = evs[b];
        P.oplist[e.br][e.bp][cnt[e.br][e.bp]++] = (uint16_t)(e.h | (e.pr << 5) | (e.seq << 12));
    }
    for (int i = 0; i < NOP; i++) {
        const int pr = NATT + i;
        for (int br = 0; br < 2; br++) P.tasks[pr][P.ntasks[pr]++] = (uint16_t)(T_OP | (br << 2) | ((i >> 1) << 3) | ((i & 1) << 7));
    }
}

}

extern "C" void kernel_launch(void* const* d_in, const int* in_sizes, int n_in, void* d_out, int out_size) {
    static Params P;
    static EncodeFn fn = nullptr;
    if (!fn) {
        void* f = nullptr;
        cudaDriverEntryPointQueryResult qr;
        cudaGetDriverEntryPoint("cuTensorMapEncodeTiled", &f, cudaEnableDefault, &qr);
        fn = (EncodeFn)f;
        cudaFuncSetAttribute(fused_mha_kernel, cudaFuncAttributeMaxDynamicSharedMemorySize, SMEM_BYTES);
    }
    memset(&P, 0, sizeof(P));
    for (int br = 0; br < 2; br++) {
        const void* x = d_in[br * 5 + 0];
        const void* k = d_in[br * 5 + 1];
        const void* v = d_in[br * 5 + 2];
        const void* wq = d_in[br * 5 + 3];
        const void* wo = d_in[br * 5 + 4];
        {
            const cuuint64_t dims[3] = {64, 16 * 32 * 512, 2}, str[2] = {256, 128};
            const cuuint32_t box[3] = {64, 64, 2};
            encode(fn, &P.tmK[br], k, 3, dims, str, box, PROMO_KV);
            encode(fn, &P.tmV[br], v, 3, dims, str, box, PROMO_KV);
        }
        { const cuuint64_t dims[2] = {512, 2304}, str[1] = {1024}; const cuuint32_t box[2] = {64, 144}; encode(fn, &P.tmX[br], x, 2, dims, str, box, PROMO_W); }
        { const cuuint64_t dims[2] = {4096, 512}, str[1] = {8192}; const cuuint32_t box[2] = {64, 64}; encode(fn, &P.tmWq[br], wq, 2, dims, str, box, PROMO_W); }
        { const cuuint64_t dims[2] = {512, 4096}, str[1] = {1024}; const cuuint32_t box[2] = {64, 64}; encode(fn, &P.tmWo[br], wo, 2, dims, str, box, PROMO_W); }
        P.K[br] = (const __nv_bfloat16*)k;
        P.V[br] = (const __nv_bfloat16*)v;
    }
    { const cuuint64_t dims[2] = {1024, 2304}, str[1] = {2048}; const cuuint32_t box[2] = {64, 144}; encode(fn, &P.tmOut, d_out, 2, dims, str, box, 0); }
    build_schedule(P, Tune{24, 3.0f, 1.2f, 0});
    fused_mha_kernel<<<2 * NPAIRS, 512, SMEM_BYTES>>>(P);
}
```

```cpp
#include <cuda_runtime.h>
#include <cuda_bf16.h>
#include <cuda.h>
#include <stdint.h>
#include <string.h>
#include <math.h>

namespace {

constexpr int NPAIRS = 66;
constexpr int MAXT = 8;
constexpr int NA = 6;
constexpr int NB = 3;
#define ORING_N 2
constexpr int ORING = ORING_N;
constexpr uint32_t A_BYTES = 16384, B_BYTES = 18432, Q_BYTES = 36864;
constexpr uint32_t OFF_A = 0;
constexpr uint32_t OFF_B = OFF_A + NA * A_BYTES;
constexpr uint32_t OFF_Q = OFF_B + NB * B_BYTES;
constexpr uint32_t OFF_BAR = OFF_Q + 2 * Q_BYTES;
constexpr uint32_t OFF_L = OFF_BAR + 512;
constexpr uint32_t SMEM_BYTES = OFF_L + 4608;
constexpr int BAR_AE = 0;
constexpr int BAR_AP = BAR_AE + NA;
constexpr int BAR_BE = BAR_AP + NA;
constexpr int BAR_XD = BAR_BE + NB;
constexpr int BAR_G = BAR_XD + 2;
constexpr int BAR_WC = BAR_G + 8;
constexpr int BAR_KS = BAR_WC + 8;
constexpr int BAR_PV = BAR_KS + 8;
constexpr int BAR_QF = BAR_PV + 8;
constexpr int BAR_QE = BAR_QF + 2;
constexpr int BAR_OS = BAR_QE + 2;
constexpr int BAR_LF = BAR_OS + 2;
constexpr int BAR_OD = BAR_LF + 1;
constexpr int BAR_OG = BAR_OD + 1;
constexpr int BAR_ZS = BAR_OG + 4;
constexpr int BAR_ZD = BAR_ZS + 1;
constexpr int NBARS = BAR_ZD + 1;
static_assert(NBARS * 8 <= 504 && OFF_BAR % 512 == 0, "barriers");
static_assert(SMEM_BYTES <= 232448, "smem");

#define LF_MODE 0
#define PROMO_KV 0
#define PROMO_W 0
#define PROF_AB0 24
#define PROF_C0 24
enum { T_Q1 = 0, T_Q2 = 1, T_OP = 2, T_OP2 = 3 };

struct alignas(64) Params {
    CUtensorMap tmK[2], tmV[2], tmX[2], tmWq[2], tmWo[2], tmOut;
    const __nv_bfloat16* K[2];
    const __nv_bfloat16* V[2];
    uint16_t tasks[NPAIRS][MAXT];
    uint16_t oplist[2][8][32];
    uint8_t delay[NPAIRS][4];
    uint8_t ntasks[NPAIRS];
    uint8_t nfirst[2][8];
    int kv_window;
};

__device__ __align__(1024) uint8_t g_O[ORING][2 * NPAIRS][Q_BYTES];
__device__ unsigned g_oready[2 * NPAIRS][8];
__device__ __align__(8) unsigned g_ofree[2 * NPAIRS][ORING][2];
__device__ unsigned g_zero[2][16][2];
__device__ unsigned g_epoch;
__device__ unsigned g_done;
#define PROF(role, idx) do { } while (0)
#define PROFD(role) do { } while (0)
#define PROFEND(role) do { } while (0)
#define PROFAB(role) do { } while (0)
#define PROFG(role) do { } while (0)

__device__ __forceinline__ uint32_t smem_u32(const void* p) { return (uint32_t)__cvta_generic_to_shared(p); }
__device__ __forceinline__ void mbar_init(uint32_t bar, uint32_t cnt) { asm volatile("mbarrier.init.shared::cta.b64 [%0], %1;" ::"r"(bar), "r"(cnt) : "memory"); }
__device__ __forceinline__ void mbar_expect_tx(uint32_t bar, uint32_t bytes) { asm volatile("mbarrier.arrive.expect_tx.shared::cta.b64 _, [%0], %1;" ::"r"(bar), "r"(bytes) : "memory"); }
__device__ __forceinline__ void mbar_arrive(uint32_t bar, uint32_t cnt) { asm volatile("mbarrier.arrive.shared::cta.b64 _, [%0], %1;" ::"r"(bar), "r"(cnt) : "memory"); }
__device__ __forceinline__ void mbar_arrive_cluster(uint32_t cbar, uint32_t cnt) { asm volatile("mbarrier.arrive.shared::cluster.b64 _, [%0], %1;" ::"r"(cbar), "r"(cnt) : "memory"); }
__device__ __forceinline__ uint32_t mapa(uint32_t addr, uint32_t cta) { uint32_t r; asm("mapa.shared::cluster.u32 %0, %1, %2;" : "=r"(r) : "r"(addr), "r"(cta)); return r; }
__device__ __forceinline__ bool mbar_test(uint32_t bar, uint32_t parity) {
    uint32_t ok;
    asm volatile("{\n.reg .pred p;\nmbarrier.test_wait.parity.shared::cta.b64 p, [%1], %2;\nselp.u32 %0, 1, 0, p;\n}" : "=r"(ok) : "r"(bar), "r"(parity) : "memory");
    return ok != 0;
}
__device__ __forceinline__ bool mbar_test2(uint32_t bar0, uint32_t par0, uint32_t bar1, uint32_t par1) {
    uint32_t ok;
    asm volatile("{\n.reg .pred p, q;\nmbarrier.test_wait.parity.shared::cta.b64 p, [%1], %2;\nmbarrier.test_wait.parity.shared::cta.b64 q, [%3], %4;\n"
                 "and.pred p, p, q;\nselp.u32 %0, 1, 0, p;\n}" : "=r"(ok) : "r"(bar0), "r"(par0), "r"(bar1), "r"(par1) : "memory");
    return ok != 0;
}
constexpr int WAIT_BUDGET = 1 << 17;
__device__ __forceinline__ void mbar_wait_b(uint32_t bar, uint32_t parity, int& budget) {
    asm volatile("{\n.reg .pred p;\nWAIT_LOOP:\nmbarrier.try_wait.parity.shared::cta.b64 p, [%1], %2, 16384;\n@p bra WAIT_DONE;\n"
                 "add.s32 %0, %0, -1;\nsetp.gt.s32 p, %0, 0;\n@p bra WAIT_LOOP;\nWAIT_DONE:\n}" : "+r"(budget) : "r"(bar), "r"(parity) : "memory");
}
#define mbar_wait(bar, parity) mbar_wait_b(bar, parity, wb)
__device__ __forceinline__ void named_sync(int id) { asm volatile("bar.sync %0, 128;" ::"r"(id) : "memory"); }
__device__ __forceinline__ void fence_async_smem() { asm volatile("fence.proxy.async.shared::cta;" ::: "memory"); }
__device__ __forceinline__ void wg_fence() { asm volatile("wgmma.fence.sync.aligned;" ::: "memory"); }
__device__ __forceinline__ void wg_commit() { asm volatile("wgmma.commit_group.sync.aligned;" ::: "memory"); }
template <int N> __device__ __forceinline__ void wg_wait() { asm volatile("wgmma.wait_group.sync.aligned %0;" ::"n"(N) : "memory"); }
__device__ __forceinline__ void touch(float (&d)[72]) {
#pragma unroll
    for (int i = 0; i < 72; i++) asm volatile("" : "+f"(d[i])::"memory");
}
__device__ __forceinline__ void fresh(float (&d)[72]) {
#pragma unroll
    for (int i = 0; i < 72; i++) d[i] = 0.f;
}
__device__ __forceinline__ uint64_t mkdesc(uint32_t addr) { return (uint64_t)(((addr & 0x3FFFF) >> 4) | (1u << 16)) | ((uint64_t)0x40000040u << 32); }

template <int TA> __device__ __forceinline__ void wgmma_n144(float (&d)[72], uint64_t da, uint64_t db, int scale_d) {
    asm volatile("{\n.reg .pred p;\nsetp.ne.b32 p, %74, 0;\n"
        "wgmma.mma_async.sync.aligned.m64n144k16.f32.bf16.bf16 "
        "{%0, %1, %2, %3, %4, %5, %6, %7, %8, %9, %10, %11, "
        "%12, %13, %14, %15, %16, %17, %18, %19, %20, %21, %22, %23, "
        "%24, %25, %26, %27, %28, %29, %30, %31, %32, %33, %34, %35, "
        "%36, %37, %38, %39, %40, %41, %42, %43, %44, %45, %46, %47, "
        "%48, %49, %50, %51, %52, %53, %54, %55, %56, %57, %58, %59, "
        "%60, %61, %62, %63, %64, %65, %66, %67, %68, %69, %70, %71}, "
        "%72, %73, p, 1, 1, %75, 0;\n}\n"
        : "+f"(d[0]), "+f"(d[1]), "+f"(d[2]), "+f"(d[3]), "+f"(d[4]), "+f"(d[5]), "+f"(d[6]), "+f"(d[7]),
          "+f"(d[8]), "+f"(d[9]), "+f"(d[10]), "+f"(d[11]), "+f"(d[12]), "+f"(d[13]), "+f"(d[14]), "+f"(d[15]),
          "+f"(d[16]), "+f"(d[17]), "+f"(d[18]), "+f"(d[19]), "+f"(d[20]), "+f"(d[21]), "+f"(d[22]), "+f"(d[23]),
          "+f"(d[24]), "+f"(d[25]), "+f"(d[26]), "+f"(d[27]), "+f"(d[28]), "+f"(d[29]), "+f"(d[30]), "+f"(d[31]),
          "+f"(d[32]), "+f"(d[33]), "+f"(d[34]), "+f"(d[35]), "+f"(d[36]), "+f"(d[37]), "+f"(d[38]), "+f"(d[39]),
          "+f"(d[40]), "+f"(d[41]), "+f"(d[42]), "+f"(d[43]), "+f"(d[44]), "+f"(d[45]), "+f"(d[46]), "+f"(d[47]),
          "+f"(d[48]), "+f"(d[49]), "+f"(d[50]), "+f"(d[51]), "+f"(d[52]), "+f"(d[53]), "+f"(d[54]), "+f"(d[55]),
          "+f"(d[56]), "+f"(d[57]), "+f"(d[58]), "+f"(d[59]), "+f"(d[60]), "+f"(d[61]), "+f"(d[62]), "+f"(d[63]),
          "+f"(d[64]), "+f"(d[65]), "+f"(d[66]), "+f"(d[67]), "+f"(d[68]), "+f"(d[69]), "+f"(d[70]), "+f"(d[71])
        : "l"(da), "l"(db), "r"(scale_d), "n"(TA));
}

__device__ __forceinline__ uint32_t pack_bf16(float lo, float hi) { uint32_t r; asm("cvt.rn.bf16x2.f32 %0, %1, %2;" : "=r"(r) : "f"(hi), "f"(lo)); return r; }
__device__ __forceinline__ uint32_t max_bf16x2(uint32_t a, uint32_t b) { uint32_t r; asm("max.bf16x2 %0, %1, %2;" : "=r"(r) : "r"(a), "r"(b)); return r; }
__device__ __forceinline__ float ex2(float x) { float r; asm volatile("ex2.approx.ftz.f32 %0, %1;" : "=f"(r) : "f"(x)); return r; }
__device__ __forceinline__ void stsm_t(uint32_t addr, uint32_t r0, uint32_t r1, uint32_t r2, uint32_t r3) {
    asm volatile("stmatrix.sync.aligned.m8n8.x4.trans.shared.b16 [%0], {%1, %2, %3, %4};" ::"r"(addr), "r"(r0), "r"(r1), "r"(r2), "r"(r3) : "memory");
}
__device__ __forceinline__ float4 lds128f(uint32_t a) { float4 v; asm volatile("ld.shared.v4.f32 {%0, %1, %2, %3}, [%4];" : "=f"(v.x), "=f"(v.y), "=f"(v.z), "=f"(v.w) : "r"(a) : "memory"); return v; }
__device__ __forceinline__ uint4 lds128u(uint32_t a) { uint4 v; asm volatile("ld.shared.v4.u32 {%0, %1, %2, %3}, [%4];" : "=r"(v.x), "=r"(v.y), "=r"(v.z), "=r"(v.w) : "r"(a) : "memory"); return v; }
__device__ __forceinline__ float2 lds64f(uint32_t a) { float2 v; asm volatile("ld.shared.v2.f32 {%0, %1}, [%2];" : "=f"(v.x), "=f"(v.y) : "r"(a) : "memory"); return v; }
__device__ __forceinline__ float rcp(float x) { float r; asm("rcp.approx.ftz.f32 %0, %1;" : "=f"(r) : "f"(x)); return r; }
__device__ __forceinline__ float lds32f(uint32_t a) { float v; asm volatile("ld.shared.f32 %0, [%1];" : "=f"(v) : "r"(a) : "memory"); return v; }
__device__ __forceinline__ void sts32f(uint32_t a, float v) { asm volatile("st.shared.f32 [%0], %1;" ::"r"(a), "f"(v) : "memory"); }
__device__ __forceinline__ void sts128f(uint32_t a, float x, float y, float z, float w) { asm volatile("st.shared.v4.f32 [%0], {%1, %2, %3, %4};" ::"r"(a), "f"(x), "f"(y), "f"(z), "f"(w) : "memory"); }
__device__ __forceinline__ void sts128u(uint32_t a, uint32_t x, uint32_t y, uint32_t z, uint32_t w) { asm volatile("st.shared.v4.u32 [%0], {%1, %2, %3, %4};" ::"r"(a), "r"(x), "r"(y), "r"(z), "r"(w) : "memory"); }

__device__ __forceinline__ void tma3d(uint32_t dst, const CUtensorMap* tm, int c0, int c1, int c2, uint32_t bar, uint64_t pol) {
    asm volatile("cp.async.bulk.tensor.3d.shared::cluster.global.mbarrier::complete_tx::bytes.L2::cache_hint [%0], [%1, {%3, %4, %5}], [%2], %6;"
                 ::"r"(dst), "l"(tm), "r"(bar), "r"(c0), "r"(c1), "r"(c2), "l"(pol) : "memory");
}
__device__ __forceinline__ void tma2d(uint32_t dst, const CUtensorMap* tm, int c0, int c1, uint32_t bar) {
    asm volatile("cp.async.bulk.tensor.2d.shared::cluster.global.mbarrier::complete_tx::bytes [%0], [%1, {%3, %4}], [%2];"
                 ::"r"(dst), "l"(tm), "r"(bar), "r"(c0), "r"(c1) : "memory");
}
__device__ __forceinline__ void tma2d_mc(uint32_t dst, const CUtensorMap* tm, int c0, int c1, uint32_t bar) {
    asm volatile("cp.async.bulk.tensor.2d.shared::cluster.global.mbarrier::complete_tx::bytes.multicast::cluster [%0], [%1, {%3, %4}], [%2], %5;"
                 ::"r"(dst), "l"(tm), "r"(bar), "r"(c0), "r"(c1), "h"((uint16_t)3) : "memory");
}
__device__ __forceinline__ void tma2d_prefetch(const CUtensorMap* tm, int c0, int c1) {
    asm volatile("cp.async.bulk.prefetch.tensor.2d.L2.global [%0, {%1, %2}];" ::"l"(tm), "r"(c0), "r"(c1) : "memory");
}
__device__ __forceinline__ void tma2d_store(const CUtensorMap* tm, int c0, int c1, uint32_t src) {
    asm volatile("cp.async.bulk.tensor.2d.global.shared::cta.bulk_group [%0, {%2, %3}], [%1];" ::"l"(tm), "r"(src), "r"(c0), "r"(c1) : "memory");
}
__device__ __forceinline__ void tma2d_add(const CUtensorMap* tm, int c0, int c1, uint32_t src) {
    asm volatile("cp.reduce.async.bulk.tensor.2d.global.shared::cta.add.bulk_group [%0, {%2, %3}], [%1];" ::"l"(tm), "r"(src), "r"(c0), "r"(c1) : "memory");
}
__device__ __forceinline__ void bulk_g2s(uint32_t dst, const void* src, uint32_t bytes, uint32_t bar) {
    asm volatile("cp.async.bulk.shared::cluster.global.mbarrier::complete_tx::bytes [%0], [%1], %2, [%3];" ::"r"(dst), "l"(src), "r"(bytes), "r"(bar) : "memory");
}
__device__ __forceinline__ void bulk_s2g(void* dst, uint32_t src, uint32_t bytes) {
    asm volatile("cp.async.bulk.global.shared::cta.bulk_group [%0], [%1], %2;" ::"l"(dst), "r"(src), "r"(bytes) : "memory");
}
__device__ __forceinline__ void bulk_prefetch(const void* src, uint32_t bytes, uint64_t pol) {
    asm volatile("cp.async.bulk.prefetch.L2.global.L2::cache_hint [%0], %1, %2;" ::"l"(src), "r"(bytes), "l"(pol) : "memory");
}
__device__ __forceinline__ bool elect() {
    uint32_t r;
    asm volatile("{\n.reg .pred p;\nelect.sync _|p, 0xffffffff;\nselp.u32 %0, 1, 0, p;\n}" : "=r"(r));
    return r != 0;
}
__device__ __forceinline__ void bulk_commit() { asm volatile("cp.async.bulk.commit_group;" ::: "memory"); }
__device__ __forceinline__ unsigned flag_wait(const unsigned* f, unsigned v, int& fb) {
    unsigned x;
    while (true) {
        asm volatile("ld.acquire.gpu.global.u32 %0, [%1];" : "=r"(x) : "l"(f) : "memory");
        if ((int)(x - v) >= 0 || --fb < 0) break;
        __nanosleep(32);
    }
    return x;
}
__device__ __forceinline__ void flag_wait2(const unsigned* f, unsigned v, int& fb) {
    while (true) {
        unsigned a, b;
        asm volatile("ld.relaxed.gpu.global.v2.u32 {%0, %1}, [%2];" : "=r"(a), "=r"(b) : "l"(f) : "memory");
        if ((int)((a - v) | (b - v)) >= 0 || --fb < 0) break;
        __nanosleep(64);
    }
    asm volatile("fence.acq_rel.gpu;" ::: "memory");
}
__device__ __forceinline__ void cluster_sync_all() { asm volatile("barrier.cluster.arrive.relaxed.aligned;\nbarrier.cluster.wait.aligned;" ::: "memory"); }
__device__ __forceinline__ unsigned read_epoch() { unsigned e; asm volatile("ld.relaxed.gpu.global.u32 %0, [%1];" : "=r"(e) : "l"(&g_epoch) : "memory"); return e; }
__device__ __forceinline__ void ack_epoch(unsigned e) {
    unsigned n;
    asm volatile("atom.acq_rel.gpu.global.inc.u32 %0, [%1], %2;" : "=r"(n) : "l"(&g_done), "r"(4u * NPAIRS - 1u) : "memory");
    if (n == 4u * NPAIRS - 1u) asm volatile("st.relaxed.gpu.global.u32 [%0], %1;" ::"l"(&g_epoch), "r"(e + 1) : "memory");
}

__device__ __forceinline__ uint32_t rel_addr(int lane, uint32_t cb0, uint32_t cb1, uint32_t other, uint32_t slot, bool next_mc) {
    const uint32_t addr = (lane == 2 ? cb1 : cb0) + 8 * (lane == 0 ? other : BAR_AE + slot);
    return lane < (next_mc ? 3 : 2) ? addr : 0u;
}
__device__ __forceinline__ void release(int lane, uint32_t addr, uint32_t cnt) {
    asm volatile("{\n.reg .pred p, q, r;\nsetp.ne.u32 r, %0, 0;\nsetp.eq.and.s32 q, %2, 2, r;\nsetp.ne.and.s32 p, %2, 2, r;\n"
                 "@q mbarrier.arrive.shared::cluster.b64 _, [%0], %1;\n@p mbarrier.arrive.shared::cta.b64 _, [%0], %1;\n}" ::"r"(addr), "r"(cnt), "r"(lane) : "memory");
}
__device__ __forceinline__ uint32_t wrap3(uint32_t s) { return s >= 3 ? s - 3 : s; }

template <int ACC> __device__ __forceinline__ void step_ab(float (&acc)[72], uint64_t da, uint64_t db, int lane, uint32_t raddr, uint32_t rcnt) {
    wg_fence();
    wgmma_n144<1>(acc, da, db, ACC);
    wgmma_n144<1>(acc, da + 128, db + 2, 1);
    if (ACC) { wg_commit(); wg_wait<1>(); release(lane, raddr, rcnt); wg_fence(); }
    wgmma_n144<1>(acc, da + 256, db + 4, 1);
    wgmma_n144<1>(acc, da + 384, db + 6, 1);
    wg_commit();
}
template <int ACC> __device__ __forceinline__ void step_c(float (&acc0)[72], float (&acc1)[72], uint64_t da, uint64_t db, int lane, uint32_t raddr, uint32_t rcnt) {
    wg_fence();
    wgmma_n144<1>(acc0, da, db, ACC);
    wgmma_n144<1>(acc1, da + 512, db, ACC);
    if (ACC) { wg_commit(); wg_wait<1>(); release(lane, raddr, rcnt); wg_fence(); }
#pragma unroll
    for (int kk = 1; kk < 4; kk++) {
        wgmma_n144<1>(acc0, da + kk * 128, db + kk * 2, 1);
        wgmma_n144<1>(acc1, da + 512 + kk * 128, db + kk * 2, 1);
    }
    wg_commit();
}
__device__ __forceinline__ void publish(uint32_t bar, int lane) {
    fence_async_smem();
    __syncwarp();
    if (lane == 0) mbar_arrive(bar, 1);
}
__device__ __forceinline__ void scale(float (&d)[72], float sc) {
#pragma unroll
    for (int i = 0; i < 72; i++) d[i] *= sc;
}
__device__ __forceinline__ void store_panel(const float (&d)[72], uint32_t lane_addr, float sc) {
#pragma unroll
    for (int jj = 0; jj < 9; jj++)
        stsm_t(lane_addr + jj * 2048, pack_bf16(d[8 * jj] * sc, d[8 * jj + 1] * sc), pack_bf16(d[8 * jj + 2] * sc, d[8 * jj + 3] * sc),
               pack_bf16(d[8 * jj + 4] * sc, d[8 * jj + 5] * sc), pack_bf16(d[8 * jj + 6] * sc, d[8 * jj + 7] * sc));
}

constexpr float L_MIN = 9.094947017729282e-13f, L_MAX = 1.152921504606847e18f;
constexpr float SM_SCALE = 0.08838834764831845f * 1.4426950408889634f;

template <int I0, int I1> __device__ __forceinline__ void exp_part(float (&d)[72]) {
#pragma unroll
    for (int i = 4 * I0; i < 4 * I1; i++) d[i] = ex2(d[i]);
}
template <int J0, int J1> __device__ __forceinline__ void out_part(const float (&d)[72], float (&sum)[36], uint32_t pa) {
#pragma unroll
    for (int jj = J0; jj < J1; jj++) {
        stsm_t(pa + jj * 2048, pack_bf16(d[8 * jj], d[8 * jj + 1]), pack_bf16(d[8 * jj + 2], d[8 * jj + 3]),
               pack_bf16(d[8 * jj + 4], d[8 * jj + 5]), pack_bf16(d[8 * jj + 6], d[8 * jj + 7]));
        sum[4 * jj] += d[8 * jj] + d[8 * jj + 2]; sum[4 * jj + 1] += d[8 * jj + 1] + d[8 * jj + 3];
        sum[4 * jj + 2] += d[8 * jj + 4] + d[8 * jj + 6]; sum[4 * jj + 3] += d[8 * jj + 5] + d[8 * jj + 7];
    }
}
__device__ __forceinline__ void reduce_sums(float (&sum)[36], uint32_t row, uint32_t bars, int lane) {
    const bool h4 = lane & 4, h8 = lane & 8, h16 = lane & 16;
    const uint32_t la = row + (lane & 3) * 144 + (h4 ? 72 : 0) + (h8 ? 36 : 0) + (h16 ? 20 : 0);
#pragma unroll
    for (int i = 0; i < 18; i++) { const float keep = h4 ? sum[18 + i] : sum[i], send = h4 ? sum[i] : sum[18 + i]; sum[i] = keep + __shfl_xor_sync(0xffffffffu, send, 4); }
#pragma unroll
    for (int i = 0; i < 9; i++) { const float keep = h8 ? sum[9 + i] : sum[i], send = h8 ? sum[i] : sum[9 + i]; sum[i] = keep + __shfl_xor_sync(0xffffffffu, send, 8); }
    const float mid = sum[4] + __shfl_xor_sync(0xffffffffu, sum[4], 16);
#pragma unroll
    for (int i = 0; i < 4; i++) { const float keep = h16 ? sum[5 + i] : sum[i], send = h16 ? sum[i] : sum[5 + i]; sts32f(la + i * 4, keep + __shfl_xor_sync(0xffffffffu, send, 16)); }
    if (!h16) sts32f(la + 16, mid);
    __syncwarp();
    if (lane == 0) mbar_arrive(bars + 8 * BAR_LF, 1);
#pragma unroll
    for (int i = 0; i < 36; i++) sum[i] = 0.f;
}
template <int ID> __device__ __forceinline__ void sched_fence(int opaque) { asm volatile("{\n.reg .pred p;\nsetp.eq.s32 p, %0, %1;\n@p exit;\n}" ::"r"(opaque), "n"(-77 - ID) : "memory"); }

__device__ __forceinline__ void mma16816(float (&c)[4], uint32_t a0, uint32_t a1, uint32_t a2, uint32_t a3, uint32_t b0, uint32_t b1) {
    asm volatile("mma.sync.aligned.m16n8k16.row.col.f32.bf16.bf16.f32 {%0, %1, %2, %3}, {%4, %5, %6, %7}, {%8, %9}, {%0, %1, %2, %3};"
                 : "+f"(c[0]), "+f"(c[1]), "+f"(c[2]), "+f"(c[3]) : "r"(a0), "r"(a1), "r"(a2), "r"(a3), "r"(b0), "r"(b1));
}
__device__ __forceinline__ uint32_t movm(uint32_t x) { uint32_t r; asm volatile("movmatrix.sync.aligned.m8n8.trans.b16 %0, %1;" : "=r"(r) : "r"(x)); return r; }
__device__ __forceinline__ void slow_head(const __nv_bfloat16* __restrict__ Kg, const __nv_bfloat16* __restrict__ Vg, uint32_t qbuf, int tid) {
    const int g = (tid & 31) >> 2, t = tid & 3;
    const uint4* Kp = reinterpret_cast<const uint4*>(Kg) + g * 16 + t;
    const uint4* Vp = reinterpret_cast<const uint4*>(Vg) + g * 16 + t;
#pragma unroll 1
    for (int qb = tid >> 5; qb < 9; qb += 4) {
        const uint32_t ra = qbuf + (qb * 16 + g) * 128;
        uint4 qa[4], qc[4];
#pragma unroll
        for (int c = 0; c < 4; c++) {
            const uint32_t a = ra + (c >> 1) * B_BYTES + (((4 * (c & 1) + t) ^ g) << 4);
            qa[c] = lds128u(a); qc[c] = lds128u(a + 1024);
        }
        float o[16][4];
#pragma unroll
        for (int i = 0; i < 16; i++) o[i][0] = o[i][1] = o[i][2] = o[i][3] = 0.f;
        float m0 = -INFINITY, m1 = -INFINITY, l0 = 0.f, l1 = 0.f;
#pragma unroll 1
        for (int kb = 0; kb < 32; kb++) {
            float sc[2][4];
#pragma unroll
            for (int n = 0; n < 2; n++) {
                sc[n][0] = sc[n][1] = sc[n][2] = sc[n][3] = 0.f;
#pragma unroll
                for (int c = 0; c < 4; c++) {
                    const uint4 k = Kp[(kb * 16 + n * 8) * 16 + 4 * c];
                    mma16816(sc[n], qa[c].x, qc[c].x, qa[c].y, qc[c].y, k.x, k.y);
                    mma16816(sc[n], qa[c].z, qc[c].z, qa[c].w, qc[c].w, k.z, k.w);
                }
            }
            float n0 = fmaxf(fmaxf(sc[0][0], sc[0][1]), fmaxf(sc[1][0], sc[1][1])), n1 = fmaxf(fmaxf(sc[0][2], sc[0][3]), fmaxf(sc[1][2], sc[1][3]));
            n0 = fmaxf(n0, __shfl_xor_sync(0xffffffffu, n0, 1)); n1 = fmaxf(n1, __shfl_xor_sync(0xffffffffu, n1, 1));
            n0 = fmaxf(n0, __shfl_xor_sync(0xffffffffu, n0, 2)); n1 = fmaxf(n1, __shfl_xor_sync(0xffffffffu, n1, 2));
            n0 = fmaxf(n0, m0); n1 = fmaxf(n1, m1);
            const float s0 = n0 == -INFINITY ? 0.f : n0, s1 = n1 == -INFINITY ? 0.f : n1;
            const float f0 = ex2(m0 - s0), f1 = ex2(m1 - s1);
            m0 = n0; m1 = n1;
#pragma unroll
            for (int n = 0; n < 2; n++) { sc[n][0] = ex2(sc[n][0] - s0); sc[n][1] = ex2(sc[n][1] - s0); sc[n][2] = ex2(sc[n][2] - s1); sc[n][3] = ex2(sc[n][3] - s1); }
            l0 = l0 * f0 + ((sc[0][0] + sc[0][1]) + (sc[1][0] + sc[1][1]));
            l1 = l1 * f1 + ((sc[0][2] + sc[0][3]) + (sc[1][2] + sc[1][3]));
            const uint32_t p0 = pack_bf16(sc[0][0], sc[0][1]), p1 = pack_bf16(sc[0][2], sc[0][3]), p2 = pack_bf16(sc[1][0], sc[1][1]), p3 = pack_bf16(sc[1][2], sc[1][3]);
#pragma unroll
            for (int c = 0; c < 4; c++) {
                const uint4 va = Vp[(kb * 16) * 16 + 4 * c], vb = Vp[(kb * 16 + 8) * 16 + 4 * c];
                const uint32_t a[4] = {va.x, va.y, va.z, va.w}, b[4] = {vb.x, vb.y, vb.z, vb.w};
#pragma unroll
                for (int r = 0; r < 4; r++) {
                    float (&d)[4] = o[4 * c + r];
                    d[0] *= f0; d[1] *= f0; d[2] *= f1; d[3] *= f1;
                    mma16816(d, p0, p1, p2, p3, movm(a[r]), movm(b[r]));
                }
            }
        }
        l0 += __shfl_xor_sync(0xffffffffu, l0, 1); l1 += __shfl_xor_sync(0xffffffffu, l1, 1);
        l0 += __shfl_xor_sync(0xffffffffu, l0, 2); l1 += __shfl_xor_sync(0xffffffffu, l1, 2);
        const float i0 = rcp(l0), i1 = rcp(l1);
#pragma unroll
        for (int c = 0; c < 4; c++) {
            const uint32_t a = ra + (c >> 1) * B_BYTES + (((4 * (c & 1) + t) ^ g) << 4);
            sts128u(a, pack_bf16(o[4 * c][0] * i0, o[4 * c][1] * i0), pack_bf16(o[4 * c + 1][0] * i0, o[4 * c + 1][1] * i0),
                    pack_bf16(o[4 * c + 2][0] * i0, o[4 * c + 2][1] * i0), pack_bf16(o[4 * c + 3][0] * i0, o[4 * c + 3][1] * i0));
            sts128u(a + 1024, pack_bf16(o[4 * c][2] * i1, o[4 * c][3] * i1), pack_bf16(o[4 * c + 1][2] * i1, o[4 * c + 1][3] * i1),
                    pack_bf16(o[4 * c + 2][2] * i1, o[4 * c + 2][3] * i1), pack_bf16(o[4 * c + 3][2] * i1, o[4 * c + 3][3] * i1));
        }
    }
}

template <int I0, int I1> __device__ __forceinline__ void init_bars(uint32_t bars) {
#pragma unroll
    for (int i = I0; i < I1; i++) {
        const uint32_t cnt = i < BAR_BE ? 8 : i < BAR_XD ? 24 : i < BAR_G ? 48 : i < BAR_WC ? 2 : i < BAR_KS ? 1 : i < BAR_QF ? 5 : i < BAR_QE ? 8 : i < BAR_OS ? 1
                           : i < BAR_LF ? 4 : i == BAR_LF ? 8 : (i >= BAR_OG && i <= BAR_ZS) ? 4 : 1;
        mbar_init(bars + 8 * i, cnt);
        if (i == BAR_KS) mbar_arrive(bars + 8 * BAR_KS, 4);
    }
}

__global__ void __cluster_dims__(2, 1, 1) __launch_bounds__(512, 1) fused_mha_kernel(const __grid_constant__ Params p) {
    extern __shared__ __align__(1024) uint8_t smem_raw[];
    const uint32_t sb = smem_u32(smem_raw);
    const uint32_t bars = sb + OFF_BAR;
    const int wg = __shfl_sync(0xffffffffu, (int)(threadIdx.x >> 7), 0);
    const int warp = __shfl_sync(0xffffffffu, (int)((threadIdx.x >> 5) & 3), 0);
    const int lane = threadIdx.x & 31;
    const int cta = blockIdx.x, pair = cta >> 1;
    const uint32_t rank = cta & 1;
    const int ntasks = p.ntasks[pair];
    int wb = WAIT_BUDGET;

    if (threadIdx.x < 11) asm volatile("prefetch.tensormap [%0];" ::"l"(&p.tmK[0] + lane) : "memory");
    if (wg == 1 && lane == 0) {
        if (warp == 0) init_bars<0, 15>(bars);
        else if (warp == 1) init_bars<15, 30>(bars);
        else if (warp == 2) init_bars<30, 45>(bars);
        else { init_bars<45, NBARS>(bars); asm volatile("st.shared.u32 [%0], %1;" ::"r"(bars + 0x1FC), "r"(0u) : "memory"); }
        asm volatile("fence.mbarrier_init.release.cluster;" ::: "memory");
    }
    const uint32_t tk0 = p.tasks[pair][0];
    __syncthreads();
    asm volatile("barrier.cluster.arrive.relaxed.aligned;" ::: "memory");
    if (wg == 0 && lane == 0 && (tk0 & 3) < T_OP) {
        const int br = (tk0 >> 2) & 1;
        if (warp == 1 || warp == 2) {
            const int row = (((tk0 >> 3) & 7) * 2 + rank) * 144;
#pragma unroll
            for (int i = 0; i < 2; i++) {
                const int k = warp == 2 ? i : 2 + i;
                tma2d(sb + (warp == 2 ? OFF_Q : OFF_B) + i * B_BYTES, &p.tmX[br], k * 64, row, bars + 8 * (BAR_G + k));
                mbar_expect_tx(bars + 8 * (BAR_G + k), B_BYTES);
            }
        } else if ((warp & 1) <= (int)(tk0 & 3)) {
            const int ring = warp & 1, c0 = ((tk0 >> 6) + ring) * 128;
#pragma unroll
            for (int i = 0; i < 3; i++) {
                const uint32_t bar = bars + 8 * (BAR_G + ring * 8 + i), dst = sb + OFF_A + (3 * ring + i) * A_BYTES;
                tma2d(dst, &p.tmWq[br], c0, i * 64, bar);
                tma2d(dst + 8192, &p.tmWq[br], c0 + 64, i * 64, bar);
                mbar_expect_tx(bar, A_BYTES);
            }
        }
    }
    __syncwarp();
    asm volatile("barrier.cluster.wait.aligned;" ::: "memory");

    if (wg == 3) {
        asm volatile("setmaxnreg.dec.sync.aligned.u32 40;");
        int fb = 1 << 22;
        if (warp == 0 || warp == 3) {
            const int ring = warp & 1;
            uint64_t pol;
            asm volatile("createpolicy.fractional.L2::evict_first.b64 %0, 1.0;" : "=l"(pol));
            uint32_t s = 3 * ring, ph = 1, ph_p = 0, used = 0;
            const unsigned t0 = (unsigned)clock();
#pragma unroll 1
            for (int t = 0; t < ntasks; t++) {
                const uint32_t tk = p.tasks[pair][t];
                const int type = tk & 3, br = (tk >> 2) & 1, bp = (tk >> 3) & 7, hh = tk >> 6;
                const int n1 = p.nfirst[br][bp], l0 = type == T_OP2 ? n1 : 0;
                const int nw = type == T_OP ? 2 * n1 : type == T_OP2 ? 64 - 2 * n1 : (ring == 1 && type == T_Q1) ? 0 : 8;
                const CUtensorMap* tm = type >= T_OP ? &p.tmWo[br] : &p.tmWq[br];
                const int c0 = ((type >= T_OP ? 2 * hh : hh) + ring) * 128 + rank * 64;
                int i = 0;
                if (t == 0 && type < T_OP && nw == 8) { i = 3; ph ^= 1; used = 1; }
#pragma unroll 1
                for (; i < nw; i++) {
                    const uint32_t bar = bars + 8 * (BAR_G + ring * 8 + (i & 7)), dst = sb + OFF_A + s * A_BYTES + rank * 8192;
                    const int c1 = type >= T_OP ? (p.oplist[br][bp][l0 + (i >> 1)] & 31) * 128 + (i & 1) * 64 : i * 64;
                    const uint32_t pp = ((ph_p >> s) & 1) ^ (used ^ 1);
                    if (!mbar_test2(bars + 8 * (BAR_AE + s), ph, bars + 8 * (BAR_AP + s), pp)) {
                        mbar_wait(bars + 8 * (BAR_AE + s), ph);
                        mbar_wait(bars + 8 * (BAR_AP + s), pp);
                    }
                    if (elect()) {
                        tma2d_mc(dst, tm, c0, c1, bar);
                        mbar_expect_tx(bar, A_BYTES);
                        if (t == 0 && type < T_OP) bulk_prefetch((ring ? p.V[br] : p.K[br]) + (size_t)((bp * 2 + rank) * 32 + hh) * 65536 + (i - 3) * 2048, 4096, pol);
                    }
                    ph_p ^= used << s;
                    if (++s == 3 * ring + 3) { s -= 3; ph ^= 1; used = 1; }
                }
                if (type >= T_OP) continue;
                if (t < 4) { const unsigned d = p.delay[pair][t] * 512u; while ((unsigned)clock() - t0 < d) __nanosleep(100); }
                const int row0 = ((bp * 2 + rank) * 32 + hh) * 512;
#pragma unroll 1
                for (int g = 0; g < 8 * (type + 1); g++) {
                    const uint32_t bar = bars + 8 * (BAR_KS + ring * 8 + (g & 7));
                    mbar_wait(bars + 8 * (BAR_AE + s), ph);
                    if (elect()) {
                        tma3d(sb + OFF_A + s * A_BYTES, ring ? &p.tmV[br] : &p.tmK[br], 0, row0 + g * 64, 0, bar, pol);
                        mbar_expect_tx(bar, A_BYTES);
                    }
                    if (++s == 3 * ring + 3) { s -= 3; ph ^= 1; used = 1; }
                }
            }
        } else if (warp == 1) {
            if (lane == 0) {
                uint32_t s = 0, ph = 1, gph = 0;
                int natt = 0, guard = 8;
                const unsigned ep = read_epoch(), base = ep * 32u;
#pragma unroll 1
                for (int t = 0; t < ntasks; t++) {
                    const uint32_t tk = p.tasks[pair][t];
                    const int type = tk & 3, br = (tk >> 2) & 1, bp = (tk >> 3) & 7;
                    if (type >= T_OP) {
                        if (t == 0) ack_epoch(ep);
                        const int n1 = p.nfirst[br][bp], l0 = type == T_OP2 ? n1 : 0, ns = type == T_OP ? 2 * n1 : 64 - 2 * n1;
                        const uint16_t* lst = &p.oplist[br][bp][l0];
                        unsigned seen = 0;
                        auto mark_free = [&](int hd) {
                            const uint32_t e = lst[hd];
                            asm volatile("st.relaxed.gpu.global.u32 [%0], %1;" ::"l"(&g_ofree[((e >> 5) & 127) * 2 + rank][(e >> 12) % ORING][tk >> 6]), "r"(base + (e >> 12) + 1) : "memory");
                        };
#pragma unroll 1
                        for (int i = 0; i < ns; i++) {
                            const uint32_t e = lst[i >> 1];
                            const int src = ((e >> 5) & 127) * 2 + rank, seq = e >> 12;
                            if ((i & 1) == 0 || (int)(seen - (base + 2 * seq + 2)) < 0) {
                                seen = flag_wait(&g_oready[src][0], base + 2 * seq + 1 + (i & 1), fb);
                                asm volatile("fence.proxy.async.global;" ::: "memory");
                            }
                            if (guard < 8) { mbar_wait(bars + 8 * (BAR_PV + guard), (natt - 1) & 1); guard++; }
                            mbar_wait(bars + 8 * (BAR_BE + s), ph);
                            bulk_g2s(sb + OFF_B + s * B_BYTES, &g_O[seq % ORING][src][(i & 1) * B_BYTES], B_BYTES, bars + 8 * (BAR_G + (i & 7)));
                            mbar_expect_tx(bars + 8 * (BAR_G + (i & 7)), B_BYTES);
                            if (i >= 4 && (i & 1) == 0) mark_free((i >> 1) - 2);
                            gph ^= 1u << (i & 7);
                            if (++s == NB) { s = 0; ph ^= 1; }
                        }
#pragma unroll 1
                        for (int i = ns - 3; i < ns; i++) {
                            mbar_wait(bars + 8 * (BAR_G + (i & 7)), ((gph >> (i & 7)) & 1) ^ 1);
                            if (i & 1) mark_free(i >> 1);
                        }
                    } else {
                        gph ^= 0xffu;
                        if (t == 0) s = 2;
#pragma unroll 1
                        for (int ii = t == 0 ? 4 : 2; ii < 6; ii++) {
                            const int i = ii == 5 ? 7 : ii;
                            if (guard < 8) { mbar_wait(bars + 8 * (BAR_PV + guard), (natt - 1) & 1); guard++; }
                            mbar_wait(bars + 8 * (BAR_BE + s), ph);
                            tma2d(sb + OFF_B + s * B_BYTES, &p.tmX[br], i * 64, (bp * 2 + rank) * 144, bars + 8 * (BAR_G + i));
                            mbar_expect_tx(bars + 8 * (BAR_G + i), B_BYTES);
                            if (++s == NB) { s = 0; ph ^= 1; }
                        }
                        if (t == 0) ack_epoch(ep);
                        if (type == T_Q2) mbar_wait(bars + 8 * (BAR_OS + (natt & 1)), (natt >> 1) & 1);
#pragma unroll 1
                        for (int e = 0; e <= type; e++) { s += 2; if (s >= NB) { s -= NB; ph ^= 1; } }
                        natt += type + 1;
                        guard = 5;
                    }
                }
            }
        } else {
            if (lane == 0) {
                int natt = 0, nq = 0, nop = 0, nz = 0;
                bool have01 = false;
                const unsigned ep = read_epoch(), base = ep * 32u;
#pragma unroll 1
                for (int t = 0; t < ntasks; t++) {
                    const uint32_t tk = p.tasks[pair][t];
                    const int type = tk & 3;
                    if (type >= T_OP) {
                        const int br = (tk >> 2) & 1, bp = (tk >> 3) & 7, ch = tk >> 6;
                        const int c0 = br * 512 + ch * 256, c1 = (bp * 2 + rank) * 144;
                        const bool add = p.nfirst[br][bp] < 32;
                        if (t == 0) ack_epoch(ep);
                        if (add) {
                            if (type == T_OP) {
                                mbar_wait(bars + 8 * BAR_ZS, nz & 1);
                                nz++;
#pragma unroll 1
                                for (int i = 0; i < 4; i++) { tma2d_store(&p.tmOut, c0 + i * 64, c1, sb + OFF_Q); bulk_commit(); asm volatile("cp.async.bulk.wait_group.read 0;" ::: "memory"); }
                                mbar_arrive(bars + 8 * BAR_ZD, 1);
                                asm volatile("cp.async.bulk.wait_group 0;" ::: "memory");
                                asm volatile("fence.proxy.async.global;" ::: "memory");
                                asm volatile("st.release.gpu.global.u32 [%0], %1;" ::"l"(&g_zero[br][bp * 2 + rank][ch]), "r"(ep + 1) : "memory");
                            } else {
                                flag_wait(&g_zero[br][bp * 2 + rank][ch], ep + 1, fb);
                                asm volatile("fence.proxy.async.global;" ::: "memory");
                            }
                        }
#pragma unroll 1
                        for (int i = 0; i < 4; i++) {
                            mbar_wait(bars + 8 * (BAR_OG + i), nop & 1);
                            if (add) tma2d_add(&p.tmOut, c0 + i * 64, c1, sb + OFF_Q + i * B_BYTES);
                            else tma2d_store(&p.tmOut, c0 + i * 64, c1, sb + OFF_Q + i * B_BYTES);
                        }
                        nop++;
                        bulk_commit();
                        asm volatile("cp.async.bulk.wait_group.read 0;" ::: "memory");
                        mbar_arrive(bars + 8 * BAR_OD, 1);
                        continue;
                    }
                    const uint32_t nk = t + 1 < ntasks ? p.tasks[pair][t + 1] : (uint32_t)T_OP;
                    auto load_x = [&](uint32_t task, int buf, int panel, int k) {
                        const uint32_t bar = bars + 8 * (BAR_G + k);
                        tma2d(sb + OFF_Q + buf * Q_BYTES + panel * B_BYTES, &p.tmX[(task >> 2) & 1], k * 64, (((task >> 3) & 7) * 2 + rank) * 144, bar);
                        mbar_expect_tx(bar, B_BYTES);
                    };
                    if (!have01) {
                        if (t != 0) { load_x(tk, natt & 1, 0, 0); load_x(tk, natt & 1, 1, 1); }
                        else mbar_wait(bars + 8 * BAR_G, 0);
                        load_x(tk, (natt + 1) & 1, 0, 5); load_x(tk, (natt + 1) & 1, 1, 6);
                    }
                    if (t == 0) ack_epoch(ep);
                    have01 = (nk & 3) < T_OP;
                    if (type == T_Q1) {
                        mbar_wait(bars + 8 * (BAR_XD + 1), nq & 1);
                        if (have01) { load_x(nk, (natt + 1) & 1, 0, 0); load_x(nk, (natt + 1) & 1, 1, 1); }
                    }
#pragma unroll 1
                    for (int e = 0; e <= type; e++, natt++) {
                        const int buf = natt & 1, slot = natt % ORING;
                        if (natt >= ORING) {
                            flag_wait2(&g_ofree[cta][slot][0], base + natt - ORING + 1, fb);
                            asm volatile("fence.proxy.async.global;" ::: "memory");
                        }
                        mbar_wait(bars + 8 * (BAR_OS + buf), (natt >> 1) & 1);
                        bulk_s2g(&g_O[slot][cta][0], sb + OFF_Q + buf * Q_BYTES, B_BYTES);
                        bulk_commit();
                        if (have01) {
                            asm volatile("cp.async.bulk.wait_group.read 0;" ::: "memory");
                            load_x(nk, buf, 0, e == type ? 5 : 0);
                        }
                        bulk_s2g(&g_O[slot][cta][B_BYTES], sb + OFF_Q + buf * Q_BYTES + B_BYTES, B_BYTES);
                        bulk_commit();
                        if (!have01) {
                            asm volatile("cp.async.bulk.wait_group 1;" ::: "memory");
                            asm volatile("fence.proxy.async.global;" ::: "memory");
                            asm volatile("st.release.gpu.global.u32 [%0], %1;" ::"l"(&g_oready[cta][0]), "r"(base + 2 * natt + 1) : "memory");
                        }
                        asm volatile("cp.async.bulk.wait_group.read 0;" ::: "memory");
                        if (have01) load_x(nk, buf, 1, e == type ? 6 : 1);
                        mbar_arrive(bars + 8 * (BAR_QE + buf), 1);
                        asm volatile("cp.async.bulk.wait_group 0;" ::: "memory");
                        asm volatile("fence.proxy.async.global;" ::: "memory");
                        asm volatile("st.release.gpu.global.u32 [%0], %1;" ::"l"(&g_oready[cta][0]), "r"(base + 2 * natt + 2) : "memory");
                    }
                    nq++;
                }
                asm volatile("cp.async.bulk.wait_group 0;" ::: "memory");
            }
        }
        __syncwarp();
        cluster_sync_all();
    } else if (wg < 2) {
        asm volatile("setmaxnreg.inc.sync.aligned.u32 144;");
        float acc[72], sum[36];
        fresh(acc);
#pragma unroll
        for (int i = 0; i < 36; i++) sum[i] = 0.f;
        uint32_t as = 0, bslot = 0, bph = 1;
        uint32_t gph = 0, pend_bar = 0;
        int natt = 0, nq = 0, nop = 0, nz = 0;
        int opaque;
        asm volatile("ld.volatile.shared.u32 %0, [%1];" : "=r"(opaque) : "r"(bars + 0x1FC));
        opaque = __shfl_sync(0xffffffffu, opaque, 0);
        const uint32_t cb0 = bars, cb1 = mapa(bars, rank ^ 1) + 8 * NA;
        const uint32_t lane_off = ((lane >> 4) * 8 + (lane & 7)) * 128 + (((2 * warp + ((lane >> 3) & 1)) ^ (lane & 7)) << 4);
        const uint32_t lrow = sb + OFF_L + (wg * 4 + warp) * 576;
        int pidx = 0, didx = PROF_AB0;
        for (int t = 0; t < ntasks; t++) {
            const uint32_t tk = p.tasks[pair][t];
            const int type = tk & 3;
            uint32_t raddr = 0;
            const uint32_t rcnt = lane == 0 ? (type == T_Q1 ? 3 : 2) : 1;
            PROFAB(wg);
            if (type >= T_OP) {
                if (pend_bar != 0) { publish(pend_bar, lane); reduce_sums(sum, lrow, bars, lane); pend_bar = 0; }
                const int n1 = p.nfirst[(tk >> 2) & 1][(tk >> 3) & 7], ns = type == T_OP ? 2 * n1 : 64 - 2 * n1;
                const bool zero = wg == 0 && type == T_OP && n1 < 32;
                fresh(acc);
#pragma unroll 1
                for (int k = 0; k < ns; k++) {
                    const uint32_t gbar = bars + 8 * (BAR_G + (k & 7)), par = (gph >> (k & 7)) & 1;
                    gph ^= 1u << (k & 7);
                    if (!mbar_test(gbar, par)) {
                        wg_wait<0>();
                        release(lane, raddr, rcnt);
                        raddr = 0;
                        mbar_wait(gbar, par);
                    }
                    const uint64_t da = mkdesc(sb + OFF_A + as * A_BYTES + wg * 8192), db = mkdesc(sb + OFF_B + bslot * B_BYTES);
                    step_ab<1>(acc, da, db, lane, raddr, rcnt);
                    raddr = rel_addr(lane, cb0, cb1, BAR_BE + bslot, as, true);
                    if (k == (zero ? 3 : ns - 1)) {
                        if (natt >= 1) mbar_wait(bars + 8 * (BAR_QE + ((natt - 1) & 1)), ((natt - 1) >> 1) & 1);
                        if (natt >= 2) mbar_wait(bars + 8 * (BAR_QE + (natt & 1)), ((natt - 2) >> 1) & 1);
                        mbar_wait(bars + 8 * BAR_OD, (nop & 1) ^ 1);
                        if (zero) {
#pragma unroll
                            for (int i = 0; i < 9; i++) sts128u(sb + OFF_Q + i * 2048 + threadIdx.x * 16, 0, 0, 0, 0);
                            publish(bars + 8 * BAR_ZS, lane);
                        }
                    }
                    as = wrap3(as + 1);
                    if (++bslot == NB) { bslot = 0; bph ^= 1; }
                }
                if (zero) { mbar_wait(bars + 8 * BAR_ZD, nz & 1); nz++; }
                wg_wait<0>();
                touch(acc);
                release(lane, raddr, rcnt);
                PROFAB(wg);
                nop++;
                store_panel(acc, sb + OFF_Q + wg * B_BYTES + lane_off, 1.0f);
                publish(bars + 8 * (BAR_OG + wg), lane);
                continue;
            }
            {
                const uint32_t q0 = sb + OFF_Q + (natt & 1) * Q_BYTES, q1 = sb + OFF_Q + ((natt + 1) & 1) * Q_BYTES;
                bool red = pend_bar != 0;
#pragma unroll
                for (int k = 0; k < 8; k++) {
                    if (!mbar_test(bars + 8 * (BAR_G + k), (gph >> k) & 1)) {
                        wg_wait<0>();
                        release(lane, raddr, rcnt);
                        raddr = 0;
                        if (k == 0 && pend_bar != 0) publish(pend_bar, lane);
                        if (k == 0) pend_bar = 0;
                        if (k < 2 && red) reduce_sums(sum, lrow, bars, lane);
                        if (k < 2) red = false;
                        mbar_wait(bars + 8 * (BAR_G + k), (gph >> k) & 1);
                    }
                    PROFG(wg);
                    const uint64_t da = mkdesc(sb + OFF_A + as * A_BYTES + wg * 8192);
                    const uint64_t db = mkdesc(k < 2 ? q0 + k * B_BYTES : (k == 5 || k == 6) ? q1 + (k - 5) * B_BYTES : sb + OFF_B + bslot * B_BYTES);
                    if (k == 0) step_ab<0>(acc, da, db, lane, 0, 0); else step_ab<1>(acc, da, db, lane, raddr, rcnt);
                    if (k == 0 && pend_bar != 0) publish(pend_bar, lane);
                    if (k == 1 && red) reduce_sums(sum, lrow, bars, lane);
                    raddr = rel_addr(lane, cb0, cb1, k < 2 ? BAR_XD : (k == 5 || k == 6) ? BAR_XD + 1 : BAR_BE + bslot, as, k + 3 < 8);
                    as = wrap3(as + 1);
                    if (k >= 2 && k != 5 && k != 6) { if (++bslot == NB) { bslot = 0; bph ^= 1; } }
                }
                pend_bar = 0;
                const bool xd = mbar_test(bars + 8 * BAR_XD, nq & 1);
                wg_wait<0>();
                touch(acc);
                release(lane, raddr, rcnt);
                PROFAB(wg);
                if (!xd) mbar_wait(bars + 8 * BAR_XD, nq & 1);
                store_panel(acc, q0 + wg * B_BYTES + lane_off, SM_SCALE);
                publish(bars + 8 * (BAR_QF + (natt & 1)), lane);
                nq++;
                gph ^= 0xffu;
            }
            uint32_t ps = bslot + wg, pph = bph;
            if (ps >= NB) { ps -= NB; pph ^= 1; }
            const int ntile = 4 * (type + 1);
            uint32_t ks = wrap3(as + wg);
            bool ready = false;
            uint64_t da = mkdesc(sb + OFF_A + ks * A_BYTES), dq = mkdesc(sb + OFF_Q + (natt & 1) * Q_BYTES);
            mbar_wait(bars + 8 * (BAR_QF + (natt & 1)), (natt >> 1) & 1);
#pragma unroll 1
            for (int it = 0; it < ntile; it++) {
                const int tt = it & 3;
                const int j = 2 * tt + wg;
                bool red = it == 4;
                if (!ready) {
                    if (pend_bar != 0) publish(pend_bar, lane);
                    pend_bar = 0;
                    if (red) reduce_sums(sum, lrow, bars, lane);
                    red = false;
                    mbar_wait(bars + 8 * (BAR_KS + j), natt & 1);
                }
                PROFD(wg);
                wg_fence();
#pragma unroll
                for (int kk = 0; kk < 8; kk++) wgmma_n144<0>(acc, da + (kk >> 2) * 512 + (kk & 3) * 2, dq + (kk >> 2) * (B_BYTES >> 4) + (kk & 3) * 2, kk != 0);
                wg_commit();
                if (lane == 0) mbar_arrive(bars + 8 * (BAR_KS + ((j + 1) & 7)), 1);
                fence_async_smem();
                __syncwarp();
                if (pend_bar != 0 && lane == 0) mbar_arrive(pend_bar, 1);
                if (red) reduce_sums(sum, lrow, bars, lane);
                uint32_t ra = rel_addr(lane, cb0, cb1, 0, ks, 2 * it + wg + 3 >= 2 * ntile);
                if (lane == 0) ra = 0;
                uint32_t pa = sb + OFF_B + ps * B_BYTES + lane_off;
                const bool pfree = mbar_test(bars + 8 * (BAR_BE + ps), pph);
                asm volatile("" : "+r"(ra), "+r"(pa));
                wg_wait<0>();
                touch(acc);
                PROFD(wg);
                exp_part<0, 1>(acc);
                release(lane, ra, 2);
                exp_part<1, 6>(acc);
                if (!pfree) mbar_wait(bars + 8 * (BAR_BE + ps), pph);
                exp_part<6, 10>(acc); out_part<0, 2>(acc, sum, pa); sched_fence<0>(opaque);
                pend_bar = bars + 8 * (BAR_PV + j);
                ks = wrap3(ks + 2);
                ps += 2; if (ps >= NB) { ps -= NB; pph ^= 1; }
                if (tt == 3) natt++;
                da = mkdesc(sb + OFF_A + ks * A_BYTES); dq = mkdesc(sb + OFF_Q + (natt & 1) * Q_BYTES);
                exp_part<10, 14>(acc); out_part<2, 4>(acc, sum, pa); sched_fence<1>(opaque);
                exp_part<14, 18>(acc); out_part<4, 6>(acc, sum, pa);
                ready = it + 1 < ntile && mbar_test(bars + 8 * (BAR_KS + ((j + 2) & 7)), natt & 1);
                sched_fence<2>(opaque);
                out_part<6, 9>(acc, sum, pa);
            }
            for (int e = 0; e <= type; e++) {
                as = wrap3(as + 2);
                bslot += 2; if (bslot >= NB) { bslot -= NB; bph ^= 1; }
            }
        }
        if (pend_bar != 0) { publish(pend_bar, lane); reduce_sums(sum, lrow, bars, lane); }
        PROFEND(wg);
        cluster_sync_all();
    } else {
        asm volatile("setmaxnreg.inc.sync.aligned.u32 184;");
        float acc0[72], acc1[72];
        uint32_t as = 3, bslot = 0;
        uint32_t gph = 0, wph = 0;
        int natt = 0, nq = 0, nop = 0;
        const uint32_t cb0 = bars, cb1 = mapa(bars, rank ^ 1) + 8 * NA;
        const uint32_t lane_off = ((lane >> 4) * 8 + (lane & 7)) * 128 + (((2 * warp + ((lane >> 3) & 1)) ^ (lane & 7)) << 4);
        const int tid = threadIdx.x & 127;
        int pidx = 0, didx = PROF_C0;
        fresh(acc0); fresh(acc1);
        for (int t = 0; t < ntasks; t++) {
            const uint32_t tk = p.tasks[pair][t];
            const int type = tk & 3, br = (tk >> 2) & 1, bp = (tk >> 3) & 7, hh = tk >> 6;
            const bool next_w = t + 1 < ntasks && (p.tasks[pair][t + 1] & 3) != T_Q1;
            PROF(2, pidx++);
            if (type >= T_OP) {
                uint32_t raddr = 0;
                const int n1 = p.nfirst[br][bp], ns = type == T_OP ? 2 * n1 : 64 - 2 * n1;
                fresh(acc0); fresh(acc1);
#pragma unroll 1
                for (int k = 0; k < ns; k++) {
                    const uint32_t gbar = bars + 8 * (BAR_G + (k & 7)), gp = (gph >> (k & 7)) & 1, wp = (wph >> (k & 7)) & 1;
                    gph ^= 1u << (k & 7); wph ^= 1u << (k & 7);
                    if (!mbar_test2(gbar, gp, gbar + 64, wp)) {
                        wg_wait<0>();
                        release(lane, raddr, 2);
                        raddr = 0;
                        mbar_wait(gbar, gp);
                        mbar_wait(gbar + 64, wp);
                    }
                    const uint64_t da = mkdesc(sb + OFF_A + as * A_BYTES), db = mkdesc(sb + OFF_B + bslot * B_BYTES);
                    step_c<1>(acc0, acc1, da, db, lane, raddr, 2);
                    raddr = rel_addr(lane, cb0, cb1, BAR_BE + bslot, as, k + 3 < ns || next_w);
                    if (++as == 6) as = 3;
                    bslot = wrap3(bslot + 1);
                }
                if (natt >= 1) mbar_wait(bars + 8 * (BAR_QE + ((natt - 1) & 1)), ((natt - 1) >> 1) & 1);
                if (natt >= 2) mbar_wait(bars + 8 * (BAR_QE + (natt & 1)), ((natt - 2) >> 1) & 1);
                mbar_wait(bars + 8 * BAR_OD, (nop & 1) ^ 1);
                wg_wait<0>();
                touch(acc0); touch(acc1);
                release(lane, raddr, 2);
                PROF(2, pidx++);
                nop++;
                store_panel(acc0, sb + OFF_Q + 2 * B_BYTES + lane_off, 1.0f);
                publish(bars + 8 * (BAR_OG + 2), lane);
                store_panel(acc1, sb + OFF_Q + 3 * B_BYTES + lane_off, 1.0f);
                publish(bars + 8 * (BAR_OG + 3), lane);
                PROF(2, pidx++);
                continue;
            }
            if (type == T_Q1) {
                bslot = wrap3(bslot + 1);
            } else {
                const uint32_t q0 = sb + OFF_Q + (natt & 1) * Q_BYTES, q1 = sb + OFF_Q + ((natt + 1) & 1) * Q_BYTES;
                uint32_t raddr = 0;
#pragma unroll
                for (int k = 0; k < 8; k++) {
                    if (!mbar_test2(bars + 8 * (BAR_G + k), (gph >> k) & 1, bars + 8 * (BAR_WC + k), (wph >> k) & 1)) {
                        wg_wait<0>();
                        release(lane, raddr, 2);
                        raddr = 0;
                        mbar_wait(bars + 8 * (BAR_G + k), (gph >> k) & 1);
                        mbar_wait(bars + 8 * (BAR_WC + k), (wph >> k) & 1);
                    }
                    PROFG(2);
                    const uint64_t da = mkdesc(sb + OFF_A + as * A_BYTES);
                    const uint64_t db = mkdesc(k < 2 ? q0 + k * B_BYTES : (k == 5 || k == 6) ? q1 + (k - 5) * B_BYTES : sb + OFF_B + bslot * B_BYTES);
                    if (k == 0) step_c<0>(acc0, acc1, da, db, lane, 0, 0); else step_c<1>(acc0, acc1, da, db, lane, raddr, 2);
                    raddr = rel_addr(lane, cb0, cb1, k < 2 ? BAR_XD : (k == 5 || k == 6) ? BAR_XD + 1 : BAR_BE + bslot, as, k + 3 < 8);
                    if (++as == 6) as = 3;
                    if (k >= 2 && k != 5 && k != 6) bslot = wrap3(bslot + 1);
                }
                wg_wait<0>();
                touch(acc0); touch(acc1);
                release(lane, raddr, 2);
                scale(acc0, SM_SCALE); scale(acc1, SM_SCALE);
                mbar_wait(bars + 8 * (BAR_XD + 1), nq & 1);
                store_panel(acc0, q1 + lane_off, 1.0f);
                store_panel(acc1, q1 + B_BYTES + lane_off, 1.0f);
                fence_async_smem();
                __syncwarp();
                if (lane == 0) mbar_arrive(bars + 8 * (BAR_QF + ((natt + 1) & 1)), 2);
                wph ^= 0xffu;
            }
            nq++;
            gph ^= 0xffu;
            PROF(2, pidx++);
#pragma unroll 1
            for (int e = 0; e <= type; e++, natt++) {
                const int buf = natt & 1;
                uint32_t raddr;
                const uint32_t rcnt = lane == 0 ? 6 : 2;
                {
                    mbar_wait(bars + 8 * BAR_PV, natt & 1);
                    PROFD(2);
                    const uint64_t da = mkdesc(sb + OFF_A + as * A_BYTES), db = mkdesc(sb + OFF_B + bslot * B_BYTES);
                    step_c<0>(acc0, acc1, da, db, lane, 0, 0);
                    if (e != 0) publish(bars + 8 * (BAR_OS + (buf ^ 1)), lane);
                    raddr = rel_addr(lane, cb0, cb1, BAR_BE + bslot, as, false);
                    PROFD(2);
                    if (++as == 6) as = 3;
                    bslot = wrap3(bslot + 1);
                }
#pragma unroll 1
                for (int j = 1; j < 8; j++) {
                    if (!mbar_test(bars + 8 * (BAR_PV + j), natt & 1)) {
                        wg_wait<0>();
                        release(lane, raddr, rcnt);
                        raddr = 0;
                        mbar_wait(bars + 8 * (BAR_PV + j), natt & 1);
                    }
                    PROFD(2);
                    const uint64_t da = mkdesc(sb + OFF_A + as * A_BYTES), db = mkdesc(sb + OFF_B + bslot * B_BYTES);
                    step_c<1>(acc0, acc1, da, db, lane, raddr, rcnt);
                    raddr = rel_addr(lane, cb0, cb1, BAR_BE + bslot, as, next_w && e == type && j >= 5);
                    PROFD(2);
                    if (++as == 6) as = 3;
                    bslot = wrap3(bslot + 1);
                }
                mbar_wait(bars + 8 * BAR_LF, natt & 1);
                PROFD(2);
                bool bad = false;
                if (tid < 72) {
                    const uint32_t a = sb + OFF_L + tid * 8;
                    float2 v[8];
#pragma unroll
                    for (int r = 0; r < 8; r++) v[r] = lds64f(a + r * 576);
                    const float l0 = ((v[0].x + v[1].x) + (v[2].x + v[3].x)) + ((v[4].x + v[5].x) + (v[6].x + v[7].x));
                    const float l1 = ((v[0].y + v[1].y) + (v[2].y + v[3].y)) + ((v[4].y + v[5].y) + (v[6].y + v[7].y));
                    bad = !(l0 >= L_MIN && l0 <= L_MAX && l1 >= L_MIN && l1 <= L_MAX);
                    asm volatile("st.shared.v2.f32 [%0], {%1, %2};" ::"r"(a), "f"(rcp(l0)), "f"(rcp(l1)) : "memory");
                }
                uint32_t anybad;
                asm volatile("{\n.reg .pred p, q;\nsetp.ne.u32 p, %1, 0;\nbar.red.or.pred q, 3, 128, p;\nselp.u32 %0, 1, 0, q;\n}" : "=r"(anybad) : "r"((uint32_t)bad) : "memory");
                PROFD(2);
                const uint32_t ia = sb + OFF_L + (lane & 3) * 144;
                float4 nx0 = lds128f(ia), nx1 = lds128f(ia + 16);
                wg_wait<0>();
                touch(acc0); touch(acc1);
                release(lane, raddr, rcnt);
                const uint32_t qb = sb + OFF_Q + buf * Q_BYTES;
                if (__any_sync(0xffffffffu, anybad)) {
                    uint32_t tk2 = p.tasks[pair][t], tid2;
                    asm volatile("mov.u32 %0, %%tid.x;" : "=r"(tid2));
                    asm volatile("" : "+r"(tk2));
                    const size_t hoff = (size_t)((((tk2 >> 3) & 7) * 2 + rank) * 32 + (tk2 >> 6) + e) * 512 * 128;
                    slow_head(p.K[(tk2 >> 2) & 1] + hoff, p.V[(tk2 >> 2) & 1] + hoff, qb, (warp << 5) | (tid2 & 31));
                } else {
#pragma unroll
                    for (int jj = 0; jj < 9; jj++) {
                        const float4 iv = nx0;
                        nx0 = nx1;
                        if (jj + 2 < 9) nx1 = lds128f(ia + (jj + 2) * 16);
                        acc0[8 * jj] *= iv.x; acc0[8 * jj + 1] *= iv.y; acc0[8 * jj + 2] *= iv.x; acc0[8 * jj + 3] *= iv.y;
                        acc0[8 * jj + 4] *= iv.z; acc0[8 * jj + 5] *= iv.w; acc0[8 * jj + 6] *= iv.z; acc0[8 * jj + 7] *= iv.w;
                        acc1[8 * jj] *= iv.x; acc1[8 * jj + 1] *= iv.y; acc1[8 * jj + 2] *= iv.x; acc1[8 * jj + 3] *= iv.y;
                        acc1[8 * jj + 4] *= iv.z; acc1[8 * jj + 5] *= iv.w; acc1[8 * jj + 6] *= iv.z; acc1[8 * jj + 7] *= iv.w;
                    }
                    store_panel(acc0, qb + lane_off, 1.0f);
                    store_panel(acc1, qb + B_BYTES + lane_off, 1.0f);
                }
                __syncwarp();
                if (e == type) publish(bars + 8 * (BAR_OS + buf), lane);
                PROFD(2);
                PROF(2, pidx++);
            }
        }
        PROFEND(2);
        cluster_sync_all();
    }
}

typedef CUresult (*EncodeFn)(CUtensorMap*, CUtensorMapDataType, cuuint32_t, void*, const cuuint64_t*, const cuuint64_t*, const cuuint32_t*, const cuuint32_t*,
                             CUtensorMapInterleave, CUtensorMapSwizzle, CUtensorMapL2promotion, CUtensorMapFloatOOBfill);

bool encode(EncodeFn fn, CUtensorMap* tm, const void* ptr, int rank, const cuuint64_t* dims, const cuuint64_t* strides, const cuuint32_t* box, int promo) {
    const cuuint32_t es[3] = {1, 1, 1};
    return fn(tm, CU_TENSOR_MAP_DATA_TYPE_BFLOAT16, rank, const_cast<void*>(ptr), dims, strides, box, es, CU_TENSOR_MAP_INTERLEAVE_NONE,
              CU_TENSOR_MAP_SWIZZLE_128B, (CUtensorMapL2promotion)promo, CU_TENSOR_MAP_FLOAT_OOB_FILL_NONE) == CUDA_SUCCESS;
}

const uint16_t kTasks[NPAIRS][MAXT] = {
    {0x01a1, 0x0002, 0x0006, 0x0000, 0x0000, 0x0000, 0x0000, 0x0000},
    {0x0098, 0x0499, 0x07b1, 0x02bd, 0x059d, 0x0067, 0x0000, 0x0000},
    {0x00b9, 0x0022, 0x0026, 0x0000, 0x0000, 0x0000, 0x0000, 0x0000},
    {0x0119, 0x0511, 0x0095, 0x039d, 0x06ad, 0x0000, 0x0000, 0x0000},
    {0x0020, 0x0319, 0x06b9, 0x0185, 0x0525, 0x07bc, 0x0000, 0x0000},
    {0x0239, 0x05a1, 0x002d, 0x0385, 0x0715, 0x0000, 0x0000, 0x0000},
    {0x0038, 0x0409, 0x0711, 0x023d, 0x0535, 0x0794, 0x0000, 0x0000},
    {0x0331, 0x0639, 0x010d, 0x043d, 0x067c, 0x007f, 0x0000, 0x0000},
    {0x0008, 0x0419, 0x07a1, 0x0285, 0x0595, 0x0017, 0x0000, 0x0000},
    {0x0101, 0x004a, 0x004e, 0x0000, 0x0000, 0x0000, 0x0000, 0x0000},
    {0x0129, 0x0521, 0x0035, 0x0315, 0x068d, 0x0000, 0x0000, 0x0000},
    {0x01b1, 0x006a, 0x006e, 0x0000, 0x0000, 0x0000, 0x0000, 0x0000},
    {0x0219, 0x0529, 0x00a5, 0x0335, 0x06a5, 0x0000, 0x0000, 0x0000},
    {0x0088, 0x0431, 0x0731, 0x0235, 0x051d, 0x07fc, 0x0000, 0x0000},
    {0x02b9, 0x0591, 0x00ad, 0x0435, 0x072d, 0x0000, 0x0000, 0x0000},
    {0x0000, 0x03b1, 0x0709, 0x021d, 0x05a5, 0x07dc, 0x0000, 0x0000},
    {0x0339, 0x0629, 0x0135, 0x0485, 0x070c, 0x0000, 0x0000, 0x0000},
    {0x00d8, 0x0481, 0x0799, 0x028d, 0x0605, 0x005f, 0x0000, 0x0000},
    {0x0201, 0x001a, 0x001e, 0x0000, 0x0000, 0x0000, 0x0000, 0x0000},
    {0x0189, 0x0501, 0x000d, 0x03bd, 0x0725, 0x0000, 0x0000, 0x0000},
    {0x0109, 0x003a, 0x003e, 0x0000, 0x0000, 0x0000, 0x0000, 0x0000},
    {0x0291, 0x0621, 0x0105, 0x041d, 0x078d, 0x0000, 0x0000, 0x0000},
    {0x0078, 0x0329, 0x0719, 0x0225, 0x04a5, 0x07b4, 0x0000, 0x0000},
    {0x0299, 0x0601, 0x013d, 0x042d, 0x0614, 0x0077, 0x0000, 0x0000},
    {0x0048, 0x0391, 0x06a1, 0x0205, 0x058d, 0x000f, 0x0000, 0x0000},
    {0x00a9, 0x0042, 0x0046, 0x0000, 0x0000, 0x0000, 0x0000, 0x0000},
    {0x00e0, 0x0491, 0x0791, 0x02ad, 0x060d, 0x002f, 0x0000, 0x0000},
    {0x0199, 0x0062, 0x0066, 0x0000, 0x0000, 0x0000, 0x0000, 0x0000},
    {0x01a9, 0x0489, 0x0025, 0x030d, 0x061d, 0x0000, 0x0000, 0x0000},
    {0x0010, 0x03a1, 0x06a9, 0x01b5, 0x04bd, 0x0784, 0x0000, 0x0000},
    {0x0281, 0x0581, 0x0085, 0x040d, 0x0735, 0x0000, 0x0000, 0x0000},
    {0x0030, 0x0411, 0x0729, 0x02a5, 0x05b5, 0x07ec, 0x0000, 0x0000},
    {0x0311, 0x0609, 0x01ad, 0x04ad, 0x074c, 0x0000, 0x0000, 0x0000},
    {0x00a0, 0x0429, 0x0739, 0x0295, 0x05bd, 0x0057, 0x0000, 0x0000},
    {0x0221, 0x0012, 0x0016, 0x0000, 0x0000, 0x0000, 0x0000, 0x0000},
    {0x0139, 0x0531, 0x009d, 0x03ad, 0x0705, 0x0000, 0x0000, 0x0000},
    {0x0121, 0x0032, 0x0036, 0x0000, 0x0000, 0x0000, 0x0000, 0x0000},
    {0x0209, 0x0539, 0x001d, 0x033d, 0x062d, 0x0000, 0x0000, 0x0000},
    {0x0040, 0x0389, 0x0681, 0x01bd, 0x0495, 0x07c4, 0x0000, 0x0000},
    {0x02b1, 0x0599, 0x0125, 0x0415, 0x07a5, 0x0000, 0x0000, 0x0000},
    {0x0070, 0x03b9, 0x0691, 0x01a5, 0x053d, 0x0007, 0x0000, 0x0000},
    {0x0301, 0x0619, 0x018d, 0x049d, 0x06f4, 0x0000, 0x0000, 0x0000},
    {0x00c8, 0x04a9, 0x0781, 0x029d, 0x0625, 0x0027, 0x0000, 0x0000},
    {0x00b1, 0x005a, 0x005e, 0x0000, 0x0000, 0x0000, 0x0000, 0x0000},
    {0x0131, 0x0509, 0x0015, 0x031d, 0x0685, 0x0000, 0x0000, 0x0000},
    {0x0231, 0x007a, 0x007e, 0x0000, 0x0000, 0x0000, 0x0000, 0x0000},
    {0x0211, 0x05b1, 0x00bd, 0x03b5, 0x073d, 0x0000, 0x0000, 0x0000},
    {0x0018, 0x0381, 0x06b1, 0x0215, 0x0505, 0x07d4, 0x0000, 0x0000},
    {0x0289, 0x05a9, 0x011d, 0x0405, 0x063c, 0x003f, 0x0000, 0x0000},
    {0x0050, 0x0399, 0x0689, 0x022d, 0x0515, 0x004f, 0x0000, 0x0000},
    {0x0229, 0x000a, 0x000e, 0x0000, 0x0000, 0x0000, 0x0000, 0x0000},
    {0x00c0, 0x04b1, 0x07a9, 0x0305, 0x0635, 0x006f, 0x0000, 0x0000},
    {0x0181, 0x002a, 0x002e, 0x0000, 0x0000, 0x0000, 0x0000, 0x0000},
    {0x0111, 0x0519, 0x00b5, 0x032d, 0x06bd, 0x0000, 0x0000, 0x0000},
    {0x0060, 0x03a9, 0x0701, 0x020d, 0x0585, 0x07ac, 0x0000, 0x0000},
    {0x02a1, 0x05b9, 0x008d, 0x0395, 0x071d, 0x0000, 0x0000, 0x0000},
    {0x0068, 0x0401, 0x0789, 0x02b5, 0x052d, 0x079c, 0x0000, 0x0000},
    {0x0309, 0x0611, 0x012d, 0x0425, 0x0654, 0x0000, 0x0000, 0x0000},
    {0x0080, 0x04a1, 0x07b9, 0x0325, 0x05ad, 0x001f, 0x0000, 0x0000},
    {0x02a9, 0x0052, 0x0056, 0x0000, 0x0000, 0x0000, 0x0000, 0x0000},
    {0x0091, 0x04b9, 0x0005, 0x03a5, 0x069d, 0x0000, 0x0000, 0x0000},
    {0x01b9, 0x0072, 0x0076, 0x0000, 0x0000, 0x0000, 0x0000, 0x0000},
    {0x0191, 0x0589, 0x003d, 0x038d, 0x0695, 0x0000, 0x0000, 0x0000},
    {0x0028, 0x0439, 0x0699, 0x0195, 0x050d, 0x07f4, 0x0000, 0x0000},
    {0x0321, 0x0631, 0x0115, 0x04b5, 0x06b4, 0x0037, 0x0000, 0x0000},
    {0x0058, 0x0421, 0x0721, 0x019d, 0x048d, 0x0047, 0x0000, 0x0000},
};
const uint8_t kNTasks[NPAIRS] = {3, 6, 3, 5, 6, 5, 6, 6, 6, 3, 5, 3, 5, 6, 5, 6, 5, 6, 3, 5, 3, 5, 6, 6, 6, 3, 6, 3, 5, 6, 5, 6, 5, 6, 3, 5, 3, 5, 6, 5, 6, 5, 6, 3, 5, 3, 5, 6, 6, 6, 3, 6, 3, 5, 6, 5, 6, 5, 6, 3, 5, 3, 5, 6, 6, 6};
const uint8_t kDelay[NPAIRS][4] = {{28,0,0,0}, {3,78,0,0}, {14,0,0,0}, {5,95,0,0}, {13,35,0,0}, {19,94,0,0}, {13,34,0,0}, {42,88,0,0}, {15,79,0,0}, {5,0,0,0}, {13,104,0,0}, {27,0,0,0}, {12,89,0,0}, {13,55,0,0}, {34,103,0,0}, {12,66,0,0}, {52,89,0,0}, {11,77,0,0}, {9,0,0,0}, {34,66,0,0}, {16,0,0,0}, {4,69,0,0}, {14,50,0,0}, {38,89,0,0}, {6,75,0,0}, {11,0,0,0}, {4,83,0,0}, {18,0,0,0}, {13,93,0,0}, {15,58,0,0}, {14,92,0,0}, {9,67,0,0}, {47,108,0,0}, {14,38,0,0}, {11,0,0,0}, {6,91,0,0}, {3,0,0,0}, {7,82,0,0}, {6,68,0,0}, {6,94,0,0}, {11,62,0,0}, {53,92,0,0}, {12,82,0,0}, {18,0,0,0}, {16,94,0,0}, {17,0,0,0}, {31,79,0,0}, {3,48,0,0}, {43,80,0,0}, {12,53,0,0}, {6,0,0,0}, {3,82,0,0}, {10,0,0,0}, {5,61,0,0}, {17,48,0,0}, {37,102,0,0}, {9,51,0,0}, {52,122,0,0}, {36,34,0,0}, {11,0,0,0}, {7,100,0,0}, {4,0,0,0}, {27,95,0,0}, {10,67,0,0}, {15,72,0,0}, {13,69,0,0}};
const uint8_t kNFirst[16] = {32, 32, 32, 32, 32, 32, 32, 32, 23, 24, 24, 25, 25, 25, 25, 25};
const uint16_t kOpList[16][32] = {
    {0x01e0, 0x04c1, 0x0124, 0x0686, 0x0248, 0x03ca, 0x0742, 0x0663, 0x052c, 0x1125, 0x1249, 0x1687, 0x13cb, 0x15ee, 0x1710, 0x152d,
     0x1232, 0x25ef, 0x2711, 0x2274, 0x23d6, 0x2233, 0x22f8, 0x3275, 0x33d7, 0x34da, 0x32f9, 0x36dc, 0x355e, 0x44db, 0x46dd, 0x455f},
    {0x0100, 0x0301, 0x01a2, 0x0266, 0x04a8, 0x0284, 0x0543, 0x060a, 0x072c, 0x1285, 0x1267, 0x14a9, 0x14ce, 0x10d0, 0x160b, 0x172d,
     0x24cf, 0x20d1, 0x2392, 0x2594, 0x27d6, 0x3393, 0x3595, 0x37d7, 0x2418, 0x31fc, 0x363a, 0x371e, 0x3419, 0x463b, 0x41fd, 0x471f},
    {0x03a0, 0x0621, 0x0782, 0x06a4, 0x07c6, 0x05c8, 0x02aa, 0x1783, 0x16a5, 0x17c7, 0x040c, 0x15c9, 0x130e, 0x12ab, 0x13f0, 0x140d,
     0x1352, 0x230f, 0x23f1, 0x2074, 0x2353, 0x21d6, 0x2738, 0x3075, 0x31d7, 0x351a, 0x30dc, 0x3739, 0x335e, 0x451b, 0x40dd, 0x435f},
    {0x05e0, 0x0821, 0x0064, 0x0188, 0x0366, 0x0022, 0x0223, 0x02ea, 0x1367, 0x1065, 0x1189, 0x108c, 0x12eb, 0x162e, 0x1110, 0x1032,
     0x208d, 0x262f, 0x26b4, 0x2111, 0x2033, 0x24f6, 0x2538, 0x36b5, 0x34f7, 0x37fa, 0x32dc, 0x3539, 0x323e, 0x47fb, 0x42dd, 0x423f},
    {0x0080, 0x06c1, 0x0448, 0x0006, 0x0484, 0x0422, 0x06ea, 0x0343, 0x080c, 0x1485, 0x1007, 0x1449, 0x16eb, 0x13ae, 0x1830, 0x180d,
     0x1752, 0x23af, 0x2831, 0x2154, 0x20b6, 0x2753, 0x22b8, 0x30b7, 0x3155, 0x331a, 0x32b9, 0x383c, 0x311e, 0x431b, 0x483d, 0x411f},
    {0x07e0, 0x0701, 0x0322, 0x0144, 0x0386, 0x0648, 0x076a, 0x1323, 0x1145, 0x1649, 0x1387, 0x176b, 0x12cc, 0x16ce, 0x1430, 0x1552,
     0x26cf, 0x22cd, 0x2194, 0x2431, 0x2553, 0x2616, 0x3195, 0x2218, 0x33ba, 0x3617, 0x33fc, 0x3219, 0x367e, 0x43bb, 0x43fd, 0x467f},
    {0x03e0, 0x0501, 0x0166, 0x0562, 0x05a8, 0x0584, 0x04ea, 0x00ec, 0x1563, 0x1585, 0x15a9, 0x1167, 0x14eb, 0x11ee, 0x10ed, 0x11b0,
     0x1672, 0x21ef, 0x21b1, 0x2474, 0x25d6, 0x2673, 0x2818, 0x3475, 0x35d7, 0x35fa, 0x31bc, 0x3819, 0x303e, 0x45fb, 0x41bd, 0x403f},
    {0x00c0, 0x02c1, 0x0042, 0x0464, 0x07a6, 0x00a8, 0x01ca, 0x1043, 0x10a9, 0x17a7, 0x1465, 0x020c, 0x11cb, 0x150e, 0x17f0, 0x120d,
     0x250f, 0x27f1, 0x2792, 0x24b4, 0x26f6, 0x20f8, 0x3793, 0x34b5, 0x36f7, 0x309a, 0x30f9, 0x343c, 0x375e, 0x409b, 0x443d, 0x475f},
    {0x4780, 0x43c2, 0x42a4, 0x5781, 0x53c3, 0x5086, 0x52a5, 0x5308, 0x510a, 0x566c, 0x6087, 0x6309, 0x610b, 0x60ae, 0x666d, 0x6212,
     0x75f4, 0x76d6, 0x7238, 0x86d7, 0x847c, 0x959b, 0x93be, 0x6610, 0x70af, 0x7611, 0x7213, 0x85f5, 0x859a, 0x8239, 0x947d, 0x94df},
    {0x4260, 0x46e2, 0x40e4, 0x4526, 0x5261, 0x56e3, 0x50e5, 0x56c8, 0x5527, 0x522a, 0x66c9, 0x638c, 0x67ce, 0x63d0, 0x622b, 0x738d,
     0x73d1, 0x77f4, 0x7358, 0x87f5, 0x815a, 0x82be, 0x841d, 0x92bf, 0x77cf, 0x7832, 0x7316, 0x8833, 0x8317, 0x8359, 0x821c, 0x915b},
    {0x4580, 0x4062, 0x4804, 0x5581, 0x5063, 0x57e6, 0x55e8, 0x5805, 0x542a, 0x67e7, 0x65e9, 0x614c, 0x642b, 0x66ee, 0x64f0, 0x714d,
     0x76ef, 0x74d2, 0x7116, 0x8635, 0x8117, 0x82f8, 0x97db, 0x90de, 0x74f1, 0x7634, 0x84d3, 0x87da, 0x80bc, 0x8739, 0x90bd, 0x95ff},
    {0x44a0, 0x4462, 0x4604, 0x54a1, 0x5463, 0x5826, 0x5605, 0x51e8, 0x554a, 0x6827, 0x61e9, 0x658c, 0x606e, 0x654b, 0x62b0, 0x6532,
     0x758d, 0x706f, 0x71b4, 0x7036, 0x8398, 0x8037, 0x9399, 0x971e, 0x96fd, 0x72b1, 0x7533, 0x81b5, 0x879a, 0x86fc, 0x979b, 0x91ff},
    {0x4380, 0x4182, 0x44e4, 0x5381, 0x5183, 0x54e5, 0x5506, 0x52c8, 0x53ea, 0x574c, 0x6507, 0x62c9, 0x63eb, 0x678e, 0x674d, 0x6730,
     0x778f, 0x7094, 0x71f6, 0x7558, 0x8095, 0x819a, 0x8559, 0x919b, 0x94ff, 0x72d2, 0x7731, 0x82d3, 0x81f7, 0x827c, 0x84fe, 0x927d},
    {0x40a0, 0x41c2, 0x4724, 0x4406, 0x50a1, 0x51c3, 0x5628, 0x5725, 0x5407, 0x534a, 0x6629, 0x66ac, 0x646e, 0x634b, 0x62f0, 0x6412,
     0x76ad, 0x746f, 0x7714, 0x7756, 0x84b8, 0x8757, 0x94b9, 0x96de, 0x93ff, 0x72f1, 0x7413, 0x8715, 0x807a, 0x81dc, 0x907b, 0x91dd},
    {0x4140, 0x46a2, 0x4204, 0x5141, 0x56a3, 0x53a6, 0x51a8, 0x570a, 0x5205, 0x63a7, 0x61a9, 0x670b, 0x618c, 0x65ce, 0x61d0, 0x6812,
     0x718d, 0x75cf, 0x71d1, 0x7813, 0x7678, 0x83f7, 0x8679, 0x853b, 0x92de, 0x70d4, 0x73f6, 0x80d5, 0x83dc, 0x881a, 0x93dd, 0x97ff},
    {0x47c0, 0x45c2, 0x42e4, 0x57c1, 0x55c3, 0x54c6, 0x50c8, 0x52e5, 0x502a, 0x64c7, 0x60c9, 0x64ac, 0x626e, 0x602b, 0x60f0, 0x74ad,
     0x726f, 0x73b2, 0x7514, 0x83b3, 0x86ba, 0x85dc, 0x80f9, 0x95dd, 0x91bf, 0x70f1, 0x7436, 0x8515, 0x8437, 0x8618, 0x96bb, 0x909e},
};

}

extern "C" void kernel_launch(void* const* d_in, const int* in_sizes, int n_in, void* d_out, int out_size) {
    static Params P;
    static EncodeFn fn = nullptr;
    if (!fn) {
        void* f = nullptr;
        cudaDriverEntryPointQueryResult qr;
        cudaGetDriverEntryPoint("cuTensorMapEncodeTiled", &f, cudaEnableDefault, &qr);
        fn = (EncodeFn)f;
        cudaFuncSetAttribute(fused_mha_kernel, cudaFuncAttributeMaxDynamicSharedMemorySize, SMEM_BYTES);
    }
    memset(&P, 0, sizeof(P));
    for (int br = 0; br < 2; br++) {
        const void* x = d_in[br * 5 + 0];
        const void* k = d_in[br * 5 + 1];
        const void* v = d_in[br * 5 + 2];
        const void* wq = d_in[br * 5 + 3];
        const void* wo = d_in[br * 5 + 4];
        {
            const cuuint64_t dims[3] = {64, 16 * 32 * 512, 2}, str[2] = {256, 128};
            const cuuint32_t box[3] = {64, 64, 2};
            encode(fn, &P.tmK[br], k, 3, dims, str, box, PROMO_KV);
            encode(fn, &P.tmV[br], v, 3, dims, str, box, PROMO_KV);
        }
        { const cuuint64_t dims[2] = {512, 2304}, str[1] = {1024}; const cuuint32_t box[2] = {64, 144}; encode(fn, &P.tmX[br], x, 2, dims, str, box, PROMO_W); }
        { const cuuint64_t dims[2] = {4096, 512}, str[1] = {8192}; const cuuint32_t box[2] = {64, 64}; encode(fn, &P.tmWq[br], wq, 2, dims, str, box, PROMO_W); }
        { const cuuint64_t dims[2] = {512, 4096}, str[1] = {1024}; const cuuint32_t box[2] = {64, 64}; encode(fn, &P.tmWo[br], wo, 2, dims, str, box, PROMO_W); }
        P.K[br] = (const __nv_bfloat16*)k;
        P.V[br] = (const __nv_bfloat16*)v;
    }
    { const cuuint64_t dims[2] = {1024, 2304}, str[1] = {2048}; const cuuint32_t box[2] = {64, 144}; encode(fn, &P.tmOut, d_out, 2, dims, str, box, 0); }
    memcpy(P.tasks, kTasks, sizeof(kTasks)); memcpy(P.ntasks, kNTasks, sizeof(kNTasks)); memcpy(P.delay, kDelay, sizeof(kDelay));
    memcpy(P.nfirst, kNFirst, sizeof(kNFirst)); memcpy(P.oplist, kOpList, sizeof(kOpList));
    fused_mha_kernel<<<2 * NPAIRS, 512, SMEM_BYTES>>>(P);
}
```
